```python
import torch

def _softmax(x, axis=-1):
    return torch.softmax(x, dim=axis)
def _gelu(x):
    return torch.nn.functional.gelu(x, approximate="tanh")
def _silu(x):
    return torch.nn.functional.silu(x)
def _sigmoid(x):
    return torch.sigmoid(x)
def _layernorm(x, axis=-1, eps=1e-5):
    m = x.mean(dim=axis, keepdim=True)
    v = x.var(dim=axis, keepdim=True, unbiased=False)
    return (x - m) / torch.sqrt(v + eps)
def _scatter_add(tgt, idx, src, axis=0):
    return tgt.clone().index_add_(axis, idx, src)
def _segment_sum(src, seg, n):
    out = torch.zeros((n,) + src.shape[1:], dtype=src.dtype)
    return out.index_add_(0, seg, src)
def _pad(x, pw):
    flat = tuple(v for pair in reversed(pw) for v in pair)
    return torch.nn.functional.pad(x, flat)

kernel_name = 'sequential_preLN__sliding_block_cached__glu_gated_geglu__decode'

def setup_inputs():

    _w = (lambda a: (lambda t: t.to(torch.bfloat16) if t.is_floating_point() else t)(torch.as_tensor(a)))
    def _A_setup():
        B, Sq, D = 2, 1, 512
        Hq, Hkv, Sk, Dh = 32, 8, 8192, 128
        assert Hq % Hkv == 0, (Hq, Hkv)
        return {
            "x": _w((lambda *s: torch.randn(*s, dtype=torch.bfloat16) * 0.05)(B, Sq, D)),
            "k_cache": _w((lambda *s: torch.randn(*s, dtype=torch.bfloat16) * 1.6)(B, Hkv, Sk, Dh)),
            "v_cache": _w((lambda *s: torch.randn(*s, dtype=torch.bfloat16) * 0.8)(B, Hkv, Sk, Dh)),
            "wq": _w((lambda *s: torch.randn(*s, dtype=torch.bfloat16) * 1.6)(D, Hq * Dh) * (D ** -0.5)),
            "wo": _w((lambda *s: torch.randn(*s, dtype=torch.bfloat16) * 0.8)(Hq * Dh, D) * ((Hq * Dh) ** -0.5)),
        }
    _A_in = _A_setup()

    def _B_setup():
        B, S, Dm, Df = 2, 1, 512, 1792
        return {
            "x": _w((lambda *s: torch.randn(*s, dtype=torch.bfloat16) * 0.05)(B, S, Dm)),
            "w_gate": _w((lambda *s: torch.randn(*s, dtype=torch.bfloat16) * 0.8)(Dm, Df) * (Dm ** -0.5)),
            "w_up": _w((lambda *s: torch.randn(*s, dtype=torch.bfloat16) * 0.8)(Dm, Df) * (Dm ** -0.5)),
            "w_down": _w((lambda *s: torch.randn(*s, dtype=torch.bfloat16) * 0.8)(Df, Dm) * (Df ** -0.5)),
        }
    _B_in = _B_setup()

    return {
        "A_x": _A_in["x"],
        "A_k_cache": _A_in["k_cache"],
        "A_v_cache": _A_in["v_cache"],
        "A_wq": _A_in["wq"],
        "A_wo": _A_in["wo"],
        "B_x": _B_in["x"],
        "B_w_gate": _B_in["w_gate"],
        "B_w_up": _B_in["w_up"],
        "B_w_down": _B_in["w_down"],
    }

def reference(A_x, A_k_cache, A_v_cache, A_wq, A_wo, B_x, B_w_gate, B_w_up, B_w_down):
    def _A_ref(x, k_cache, v_cache, wq, wo):
        B, Sq, D = x.shape
        Hq, Dh = 32, 128
        Hkv, Sk = k_cache.shape[1], k_cache.shape[2]
        W = min(4096, max(256, Sk // 4))
        rep = Hq // Hkv
        q = (lambda x, *d: x.permute(*d))((x @ wq).reshape(B, Sq, Hq, Dh), 0, 2, 1, 3)
        k = (lambda x, n, axis: torch.repeat_interleave(x, n, dim=axis))(k_cache[:, :, Sk - W:, :], rep, axis=1)
        v = (lambda x, n, axis: torch.repeat_interleave(x, n, dim=axis))(v_cache[:, :, Sk - W:, :], rep, axis=1)
        scores = torch.einsum("bhqd,bhkd->bhqk", q, k) * (Dh ** -0.5)
        p = _softmax(scores, axis=-1)
        o = torch.einsum("bhqk,bhkd->bhqd", p, v)
        return (lambda x, *d: x.permute(*d))(o, 0, 2, 1, 3).reshape(B, Sq, Hq * Dh) @ wo

    def _B_ref(x, w_gate, w_up, w_down):
        g = torch.einsum("bsd,df->bsf", x, w_gate)
        u = torch.einsum("bsd,df->bsf", x, w_up)
        h = _gelu(g) * u
        return torch.einsum("bsf,fd->bsd", h, w_down)

    x = A_x
    h = x + _A_ref(_layernorm(x, axis=-1), A_k_cache, A_v_cache, A_wq, A_wo)
    h2 = h + _B_ref(_layernorm(h, axis=-1), B_w_gate, B_w_up, B_w_down)
    return h2
```

```cpp
#include <cuda_runtime.h>
#include <cuda_bf16.h>
#include <cuda.h>
#include <stdint.h>

namespace {

constexpr int kAttn = 64, kMlp = 56, kCtas = kAttn + kMlp;
constexpr int SLOT = 16384;
constexpr int kBig = 13, kSmall = 6;
constexpr int A_XN = 0;
constexpr int A_O = A_XN + 2080;
constexpr int A_Q = A_O + 2080;
constexpr int A_P = A_Q + 1088;
constexpr int A_RS = A_P + 4160;
constexpr int A_OP = A_RS + 2048;
constexpr int A_ST = A_OP + 2176;
constexpr int A_WM = A_ST + 128;
constexpr int A_WS = A_WM + 128;
constexpr int A_GP = A_WS + 128;
constexpr int A_END = A_GP + 1024;
constexpr int M_DOWN = 65536;
constexpr int M_H = 0;
constexpr int M_PART = M_H + 2080;
constexpr int M_CSP = M_PART + 6144;
constexpr int M_CS = M_CSP + 2048;
constexpr int M_HH = M_CS + 256;
constexpr int M_ST = M_HH + 160;
constexpr int M_G3 = M_ST + 16;
constexpr int M_SP = M_G3 + 4096;
constexpr int M_END = M_SP + 128;
constexpr int OFF_BAR = ((A_END > M_END ? A_END : M_END) + 15) / 16 * 16;
constexpr int OFF_FLAG = OFF_BAR + 37 * 8;
constexpr int OFF_PROF = OFF_FLAG + 8;
constexpr int MISC_BYTES = OFF_PROF + 64;
__host__ __device__ constexpr int threads(int) { return 288; }
constexpr int smem_bytes(int nslot) { return nslot * SLOT + MISC_BYTES + 1024; }

constexpr int POLL_LIMIT = 200000;
constexpr int MBAR_LIMIT = 2000000;

struct Params {
    const __nv_bfloat16* x;
    __nv_bfloat16* out;
    unsigned* epoch;
    float* attn_part;
    float* out_part;
    int mlp_d0, mlp_dstep, mlp_n0, mlp_d1, mlp_dstep1, first_pass, depth;
    int poll_n, poll_t0, poll_dt, fin_n, fin_t0;
};

__device__ unsigned g_epoch;
__device__ __align__(1024) float g_mail[(8 + 32) * 1024];
#define PROF(i) do {} while (0)
#define PROF_DUMP() do {} while (0)
#define PROFG(i) do {} while (0)
#define PROFL(i) do {} while (0)
__device__ __forceinline__ uint32_t clock32() { uint32_t c; asm volatile("mov.u32 %0, %%clock;" : "=r"(c) :: "memory"); return c; }

__device__ __forceinline__ uint32_t s2u(const void* p) { return (uint32_t)__cvta_generic_to_shared(p); }
__device__ __forceinline__ void mbar_init(uint32_t a, int c) { asm volatile("mbarrier.init.shared::cta.b64 [%0], %1;" ::"r"(a), "r"(c) : "memory"); }
__device__ __forceinline__ void mbar_expect(uint32_t a, uint32_t b) { asm volatile("mbarrier.arrive.expect_tx.shared::cta.b64 _, [%0], %1;" ::"r"(a), "r"(b) : "memory"); }
__device__ __forceinline__ void mbar_arrive(uint32_t a) { asm volatile("mbarrier.arrive.shared::cta.b64 _, [%0];" ::"r"(a) : "memory"); }
__device__ __forceinline__ void mbar_wait(uint32_t a, uint32_t ph) {
    uint32_t ok; int it = 0;
    do {
        asm volatile("{ .reg .pred p; mbarrier.try_wait.parity.shared::cta.b64 p, [%1], %2; selp.u32 %0, 1, 0, p; }" : "=r"(ok) : "r"(a), "r"(ph) : "memory");
    } while (!ok && ++it < MBAR_LIMIT);
}
__device__ __forceinline__ void mbar_wait_cl(uint32_t a, uint32_t ph) {
    uint32_t ok; int it = 0;
    do {
        asm volatile("{ .reg .pred p; mbarrier.try_wait.parity.acquire.cluster.shared::cta.b64 p, [%1], %2; selp.u32 %0, 1, 0, p; }" : "=r"(ok) : "r"(a), "r"(ph) : "memory");
    } while (!ok && ++it < MBAR_LIMIT);
}
__device__ __forceinline__ void tma2d(uint32_t dst, const CUtensorMap* m, int c0, int c1, uint32_t bar) {
    asm volatile("cp.async.bulk.tensor.2d.shared::cluster.global.mbarrier::complete_tx::bytes [%0], [%1, {%3, %4}], [%2];"
                 ::"r"(dst), "l"(m), "r"(bar), "r"(c0), "r"(c1) : "memory");
}
__device__ __forceinline__ void tma3d(uint32_t dst, const CUtensorMap* m, int c0, int c1, int c2, uint32_t bar) {
    asm volatile("cp.async.bulk.tensor.3d.shared::cluster.global.mbarrier::complete_tx::bytes [%0], [%1, {%3, %4, %5}], [%2];"
                 ::"r"(dst), "l"(m), "r"(bar), "r"(c0), "r"(c1), "r"(c2) : "memory");
}
__device__ __forceinline__ uint32_t mapa(uint32_t a, uint32_t rank) { uint32_t r; asm("mapa.shared::cluster.u32 %0, %1, %2;" : "=r"(r) : "r"(a), "r"(rank)); return r; }
__device__ __forceinline__ void st_async4(uint32_t dst, uint32_t a, uint32_t b, uint32_t c, uint32_t d, uint32_t bar) {
    asm volatile("st.async.weak.shared::cluster.mbarrier::complete_tx::bytes.v4.b32 [%0], {%1,%2,%3,%4}, [%5];"
                 ::"r"(dst), "r"(a), "r"(b), "r"(c), "r"(d), "r"(bar) : "memory");
}
__device__ __forceinline__ void ldsm4(uint32_t (&r)[4], uint32_t a) {
    asm volatile("ldmatrix.sync.aligned.m8n8.x4.shared.b16 {%0,%1,%2,%3}, [%4];" : "=r"(r[0]), "=r"(r[1]), "=r"(r[2]), "=r"(r[3]) : "r"(a) : "memory");
}
__device__ __forceinline__ void ldsm4t(uint32_t (&r)[4], uint32_t a) {
    asm volatile("ldmatrix.sync.aligned.m8n8.x4.trans.shared.b16 {%0,%1,%2,%3}, [%4];" : "=r"(r[0]), "=r"(r[1]), "=r"(r[2]), "=r"(r[3]) : "r"(a) : "memory");
}
__device__ __forceinline__ void mma(float (&c)[4], uint32_t a0, uint32_t a1, uint32_t a2, uint32_t a3, uint32_t b0, uint32_t b1) {
    asm volatile("mma.sync.aligned.m16n8k16.row.col.f32.bf16.bf16.f32 {%0,%1,%2,%3}, {%4,%5,%6,%7}, {%8,%9}, {%0,%1,%2,%3};"
                 : "+f"(c[0]), "+f"(c[1]), "+f"(c[2]), "+f"(c[3]) : "r"(a0), "r"(a1), "r"(a2), "r"(a3), "r"(b0), "r"(b1));
}
__device__ __forceinline__ void bar_sync(int id, int n) { asm volatile("bar.sync %0, %1;" ::"r"(id), "r"(n) : "memory"); }
__device__ __forceinline__ void bar_arrive(int id, int n) { asm volatile("bar.arrive %0, %1;" ::"r"(id), "r"(n) : "memory"); }
__device__ __forceinline__ void cluster_arrive() { asm volatile("barrier.cluster.arrive.relaxed.aligned;" ::: "memory"); }
__device__ __forceinline__ void cluster_wait() { asm volatile("barrier.cluster.wait.acquire.aligned;" ::: "memory"); }
__device__ __forceinline__ uint32_t pack2(float lo, float hi) { uint32_t r; asm("cvt.rn.bf16x2.f32 %0, %1, %2;" : "=r"(r) : "f"(hi), "f"(lo)); return r; }
__device__ __forceinline__ float bfr(float v) { return __uint_as_float(pack2(0.f, v)); }
__device__ __forceinline__ float bflo(uint32_t v) { return __uint_as_float(v << 16); }
__device__ __forceinline__ float bfhi(uint32_t v) { return __uint_as_float(v & 0xffff0000u); }
__device__ __forceinline__ float ex2(float v) { float r; asm("ex2.approx.ftz.f32 %0, %1;" : "=f"(r) : "f"(v)); return r; }
__device__ __forceinline__ uint4 ld_poll(const float* p) {
    uint4 v;
    asm volatile("ld.relaxed.gpu.global.v4.u32 {%0,%1,%2,%3}, [%4];" : "=r"(v.x), "=r"(v.y), "=r"(v.z), "=r"(v.w) : "l"(p) : "memory");
    return v;
}
__device__ __forceinline__ void st_tag4(float* p, float a, float b, float c, float d, uint32_t tag, int mode = 0) {
    const uint32_t x = (__float_as_uint(a) & ~1u) | tag, y = (__float_as_uint(b) & ~1u) | tag;
    const uint32_t z = (__float_as_uint(c) & ~1u) | tag, u = (__float_as_uint(d) & ~1u) | tag;
    if (mode) {
        asm volatile("{ .reg .b128 t, o; mov.b128 t, {%1, %2}; atom.relaxed.gpu.global.exch.b128 o, [%0], t; }" ::"l"(p),
                     "l"((unsigned long long)x | ((unsigned long long)y << 32)), "l"((unsigned long long)z | ((unsigned long long)u << 32)) : "memory");
    } else {
        asm volatile("st.relaxed.gpu.global.v4.u32 [%0], {%1,%2,%3,%4};" ::"l"(p), "r"(x), "r"(y), "r"(z), "r"(u) : "memory");
    }
}
__device__ __forceinline__ uint32_t pack_tag(float hi, float lo, uint32_t tag, uint32_t trnd) {
    return pack2(0.f, hi) | (((__float_as_uint(lo) + trnd) >> 17) << 1) | tag;
}
__device__ __forceinline__ void st_mail2(float* p, uint32_t x, uint32_t y) {
    asm volatile("st.relaxed.gpu.global.v2.u32 [%0], {%1,%2};" ::"l"(p), "r"(x), "r"(y) : "memory");
}
__device__ __forceinline__ uint2 ld_poll2(const float* p) {
    uint2 v;
    asm volatile("ld.relaxed.gpu.global.v2.u32 {%0,%1}, [%2];" : "=r"(v.x), "=r"(v.y) : "l"(p) : "memory");
    return v;
}
__device__ __forceinline__ void lds4(float (&v)[4], uint32_t a) {
    asm volatile("ld.shared.v4.f32 {%0,%1,%2,%3}, [%4];" : "=f"(v[0]), "=f"(v[1]), "=f"(v[2]), "=f"(v[3]) : "r"(a) : "memory");
}
__device__ __forceinline__ uint4 lds4u(uint32_t a) {
    uint4 v; asm volatile("ld.shared.v4.u32 {%0,%1,%2,%3}, [%4];" : "=r"(v.x), "=r"(v.y), "=r"(v.z), "=r"(v.w) : "r"(a) : "memory"); return v;
}
__device__ __forceinline__ float lds1(uint32_t a) { float v; asm volatile("ld.shared.f32 %0, [%1];" : "=f"(v) : "r"(a) : "memory"); return v; }
__device__ __forceinline__ uint32_t lds1u(uint32_t a) { uint32_t v; asm volatile("ld.shared.u32 %0, [%1];" : "=r"(v) : "r"(a) : "memory"); return v; }
__device__ __forceinline__ void sts1(uint32_t a, float v) { asm volatile("st.shared.f32 [%0], %1;" ::"r"(a), "f"(v) : "memory"); }
__device__ __forceinline__ void sts2(uint32_t a, float v, float w) { asm volatile("st.shared.v2.f32 [%0], {%1,%2};" ::"r"(a), "f"(v), "f"(w) : "memory"); }
__device__ __forceinline__ void sts16(uint32_t a, float v) {
    asm volatile("{ .reg .b16 lo, hi; mov.b32 {lo, hi}, %1; st.shared.u16 [%0], lo; }" ::"r"(a), "r"(pack2(v, 0.f)) : "memory");
}
__device__ __forceinline__ void sts4u(uint32_t a, uint32_t x, uint32_t y, uint32_t z, uint32_t w) {
    asm volatile("st.shared.v4.u32 [%0], {%1,%2,%3,%4};" ::"r"(a), "r"(x), "r"(y), "r"(z), "r"(w) : "memory");
}

template <int N>
__device__ __forceinline__ float tree_sum(float (&f)[N]) {
#pragma unroll
    for (int d = 1; d < N; d <<= 1)
#pragma unroll
        for (int i = 0; i + d < N; i += 2 * d) f[i] += f[i + d];
    return f[0];
}
__device__ __forceinline__ void spin_until(uint32_t t0, uint32_t due) { while (clock32() - t0 < due) {} }
__device__ __forceinline__ bool tag_bad(const uint4& v, uint32_t tmask) {
    return __any_sync(0xffffffffu, (((v.x ^ tmask) | (v.y ^ tmask)) | ((v.z ^ tmask) | (v.w ^ tmask))) & 1u);
}
__device__ __forceinline__ uint4 poll_packet(const float* src, uint32_t tmask, uint32_t gap) {
    uint4 v = ld_poll(src);
#pragma unroll 1
    for (int it = 0; it < POLL_LIMIT && tag_bad(v, tmask); it++) {
        if (gap) spin_until(clock32(), gap);
        v = ld_poll(src);
    }
    return v;
}

__device__ __forceinline__ float rcp_(float v) { float r; asm("rcp.approx.ftz.f32 %0, %1;" : "=f"(r) : "f"(v)); return r; }
__device__ __forceinline__ float sqrt_(float v) { float r; asm("sqrt.approx.ftz.f32 %0, %1;" : "=f"(r) : "f"(v)); return r; }
__device__ __forceinline__ float ln_rden(float var) { return rcp_(bfr(sqrt_(bfr(bfr(var) + 1e-5f)))); }

template <int NSLOT>
__global__ void __launch_bounds__(threads(NSLOT), NSLOT <= 6 ? 2 : 1)
fused_decode(const __grid_constant__ CUtensorMap tm_wq, const __grid_constant__ CUtensorMap tm_k,
             const __grid_constant__ CUtensorMap tm_v, const __grid_constant__ CUtensorMap tm_wo,
             const __grid_constant__ CUtensorMap tm_g, const __grid_constant__ CUtensorMap tm_u,
             const __grid_constant__ CUtensorMap tm_d, const Params p) {
    constexpr int kThreads = threads(NSLOT);
    extern __shared__ uint8_t smem_raw[];
    const uint32_t sb = (s2u(smem_raw) + 1023u) & ~1023u;
    const uint32_t mb_ = sb + NSLOT * SLOT;
    const int t = threadIdx.x, w = t >> 5, lane = t & 31, grp = lane >> 2, hq = lane & 3;
    const int cta = blockIdx.x, r = cta & 7, cl = cta >> 3;
    const uint32_t bar0 = mb_ + OFF_BAR;
    const uint32_t t_start = clock32();
#define FULL(s) (bar0 + 8 * (s))
#define EMPTY(s) (bar0 + 128 + 8 * (s))
#define XBAR(i) (bar0 + 256 + 8 * (i))
    if (t == 256) {
        mbar_init(FULL(0), 1);
        if (cta < kAttn) {
            asm volatile("fence.mbarrier_init.release.cluster;" ::: "memory");
            mbar_expect(FULL(0), SLOT);
            tma2d(sb, &tm_wq, 64 * cta, 0, FULL(0));
        }
#pragma unroll
        for (int s = 1; s < NSLOT; s++) mbar_init(FULL(s), 1);
#pragma unroll
        for (int s = 0; s < NSLOT; s++) mbar_init(EMPTY(s), 8);
        asm volatile("fence.mbarrier_init.release.cluster;" ::: "memory");
    }
    if (t == 64) {
#pragma unroll
        for (int i = 0; i < 5; i++) mbar_init(XBAR(i), 1);
        sts2(mb_ + OFF_FLAG, 0.f, 0.f);
        asm volatile("fence.mbarrier_init.release.cluster;" ::: "memory");
        mbar_expect(XBAR(0), 1024);
        mbar_expect(XBAR(1), 128);
        mbar_expect(XBAR(2), cta < kAttn ? 2048 : 128);
        mbar_expect(XBAR(3), 2048);
    }
    __syncwarp();
    cluster_arrive();

    if (cta < kAttn) {
        const int g = cl, b = r >> 2, j = r & 3;
        if (w == 8) {
            bar_arrive(0, kThreads);
            if (lane == 0) {
                const int kvrow = (b * 8 + g) * 8192 + 6144 + 512 * j - 256;
                const int depth = p.depth;
                int s = 1, ph = 1, sf = 0, phf = 0;
#pragma unroll 1
                for (int i = 1; i < 24; i++) {
                    if (i >= NSLOT) mbar_wait(EMPTY(s), ph);
                    if (i >= depth) { mbar_wait(FULL(sf), phf); if (++sf == NSLOT) { sf = 0; phf ^= 1; } }
                    mbar_expect(FULL(s), SLOT);
                    const uint32_t dst = sb + s * SLOT;
                    if (i < 4) tma2d(dst, &tm_wq, 64 * cta, 128 * i, FULL(s));
                    else if (i < 20) tma3d(dst, i < 12 ? &tm_k : &tm_v, 0, kvrow + 64 * (i < 12 ? i : i - 8), 0, FULL(s));
                    else tma2d(dst, &tm_wo, 64 * r, 512 * g + 128 * (i - 20), FULL(s));
                    if (++s == NSLOT) { s = 0; ph ^= 1; }
                }
                PROF(8);
                PROF_DUMP();
            }
            __syncwarp();
            cluster_wait();
        } else {
            if (w < 2) {
                const uint4* xp = reinterpret_cast<const uint4*>(p.x + w * 512 + lane * 16);
                const uint4 xa = __ldg(xp), xb = __ldg(xp + 1);
                const uint32_t u[8] = {xa.x, xa.y, xa.z, xa.w, xb.x, xb.y, xb.z, xb.w};
                float v[16], f[16];
#pragma unroll
                for (int i = 0; i < 8; i++) { v[2 * i] = bflo(u[i]); v[2 * i + 1] = bfhi(u[i]); }
#pragma unroll
                for (int i = 0; i < 16; i++) f[i] = v[i];
                float sm = tree_sum(f);
#pragma unroll
                for (int o = 16; o; o >>= 1) sm += __shfl_xor_sync(0xffffffffu, sm, o);
                const float mean = sm * (1.f / 512.f);
#pragma unroll
                for (int i = 0; i < 16; i++) { const float d = v[i] - mean; f[i] = d * d; }
                float sq = tree_sum(f);
#pragma unroll
                for (int o = 16; o; o >>= 1) sq += __shfl_xor_sync(0xffffffffu, sq, o);
                const float mb = bfr(mean), rden = ln_rden(sq * (1.f / 512.f));
                uint32_t o[8];
#pragma unroll
                for (int i = 0; i < 8; i++) {
                    const uint32_t c = pack2(v[2 * i] - mb, v[2 * i + 1] - mb);
                    o[i] = pack2(bflo(c) * rden, bfhi(c) * rden);
                }
                const uint32_t d = mb_ + A_XN + w * 1040 + lane * 32;
                sts4u(d, o[0], o[1], o[2], o[3]);
                sts4u(d + 16, o[4], o[5], o[6], o[7]);
            }
            unsigned ep;
            asm volatile("ld.relaxed.gpu.global.u32 %0, [%1];" : "=r"(ep) : "l"(p.epoch) : "memory");
            uint2 xr;
            asm volatile("ld.global.nc.v2.u32 {%0,%1}, [%2];" : "=r"(xr.x), "=r"(xr.y) : "l"(p.x + (hq >> 1) * 512 + 16 * (cta >> 1) + 4 * (cta & 1) + (hq & 1) * 8));
            const int mt = w & 3, hp = w >> 2, h0 = 2 * (hq & 1);
            const int mi = lane >> 3, rr = (lane & 7) + (mi >> 1) * 8;
            const uint32_t act_off = (lane & 7) * 1040 + hp * 128 + mi * 16;
            const uint32_t wt_off = sb + (64 * hp + rr) * 128 + (((2 * mt + (mi & 1)) ^ (rr & 7)) << 4);
            uint32_t gp_st = mb_ + A_GP + hp * 512 + (16 * mt + grp) * 4;
            constexpr float L2E = 1.4426950408889634f;
            bar_sync(0, kThreads);
            PROF(0);
            {
                float acc[2][4] = {};
#pragma unroll 1
                for (int i = 0; i < 4; i++) {
                    uint32_t bf[2][4];
                    ldsm4(bf[0], mb_ + A_XN + act_off + i * 256);
                    ldsm4(bf[1], mb_ + A_XN + act_off + i * 256 + 64);
                    mbar_wait(FULL(i), 0);
#pragma unroll
                    for (int k = 0; k < 4; k++) {
                        uint32_t a[4];
                        ldsm4t(a, wt_off + i * SLOT + k * 2048);
                        mma(acc[k & 1], a[0], a[1], a[2], a[3], bf[k >> 1][(k & 1) * 2], bf[k >> 1][(k & 1) * 2 + 1]);
                    }
                    __syncwarp();
                    if (lane == 0) mbar_arrive(EMPTY(i));
                }
                if (hq == 0) {
                    sts1(gp_st, acc[0][0] + acc[1][0]); sts1(gp_st + 256, acc[0][1] + acc[1][1]);
                    sts1(gp_st + 32, acc[0][2] + acc[1][2]); sts1(gp_st + 256 + 32, acc[0][3] + acc[1][3]);
                }
                cluster_wait();
                bar_sync(1, 256);
                if (w < 2) {
                    const int tg = t >> 3, pc = t & 7;
                    const uint32_t src = mb_ + A_GP + (tg >> 2) * 256 + pc * 32;
                    float u0[4], u1[4], v0[4], v1[4];
                    lds4(u0, src); lds4(u1, src + 16); lds4(v0, src + 512); lds4(v1, src + 512 + 16);
                    st_async4(mapa(mb_ + A_Q + (r >> 1) * 272 + (r & 1) * 128 + pc * 16, tg), pack2(u0[0] + v0[0], u0[1] + v0[1]),
                              pack2(u0[2] + v0[2], u0[3] + v0[3]), pack2(u1[0] + v1[0], u1[1] + v1[1]), pack2(u1[2] + v1[2], u1[3] + v1[3]),
                              mapa(XBAR(0), tg));
                }
            }
            if (w == 2 && (p.poll_n & 2)) st_tag4(p.attn_part + g * 1024 + r * 128 + lane * 4, 0.f, 0.f, 0.f, 0.f, ep & 1);
            PROF(1);
            int s = 4, ph = 0;
            float sc[4][4] = {};
            {
                mbar_wait(XBAR(0), 0);
                PROF(2);
                uint32_t qf[4][4];
#pragma unroll
                for (int i = 0; i < 4; i++) ldsm4(qf[i], mb_ + A_Q + (lane & 7) * 272 + i * 64 + (lane >> 3) * 16);
                const int row = 16 * mt + (lane & 7) + ((lane >> 3) & 1) * 8;
                const uint32_t x0a = row * 128 + ((((lane >> 4) ^ (row & 7))) << 4);
#pragma unroll 1
                for (int c = 0; c < 8; c++) {
                    if ((c & 1) == hp) {
                        mbar_wait(FULL(s), ph);
                        float s0[4] = {}, s1[4] = {};
                        const uint32_t kb = sb + s * SLOT;
#pragma unroll
                        for (int ks = 0; ks < 8; ks++) {
                            uint32_t a[4];
                            ldsm4(a, kb + (ks >> 2) * 8192 + (x0a ^ ((ks & 3) << 5)));
                            if (ks & 1) mma(s1, a[0], a[1], a[2], a[3], qf[ks >> 1][2], qf[ks >> 1][3]);
                            else mma(s0, a[0], a[1], a[2], a[3], qf[ks >> 1][0], qf[ks >> 1][1]);
                        }
#pragma unroll
                        for (int k = 0; k < 3; k++)
#pragma unroll
                            for (int e = 0; e < 4; e++) sc[k][e] = sc[k + 1][e];
                        const uint32_t r1 = pack2(s0[0] + s1[0], s0[1] + s1[1]), r3 = pack2(s0[2] + s1[2], s0[3] + s1[3]);
                        const uint32_t r2 = pack2(bflo(r1) * 0.08838834764831845f, bfhi(r1) * 0.08838834764831845f);
                        const uint32_t r4 = pack2(bflo(r3) * 0.08838834764831845f, bfhi(r3) * 0.08838834764831845f);
                        sc[3][0] = bflo(r2); sc[3][1] = bfhi(r2); sc[3][2] = bflo(r4); sc[3][3] = bfhi(r4);
                        __syncwarp();
                        if (lane < 2) mbar_arrive(EMPTY(s));
                    }
                    if (++s == NSLOT) { s = 0; ph ^= 1; }
                }
            }
            PROF(3);
            {
                float m0 = fmaxf(fmaxf(fmaxf(sc[0][0], sc[1][0]), fmaxf(sc[2][0], sc[3][0])), fmaxf(fmaxf(sc[0][2], sc[1][2]), fmaxf(sc[2][2], sc[3][2])));
                float m1 = fmaxf(fmaxf(fmaxf(sc[0][1], sc[1][1]), fmaxf(sc[2][1], sc[3][1])), fmaxf(fmaxf(sc[0][3], sc[1][3]), fmaxf(sc[2][3], sc[3][3])));
#pragma unroll
                for (int o = 4; o <= 16; o <<= 1) {
                    m0 = fmaxf(m0, __shfl_xor_sync(0xffffffffu, m0, o));
                    m1 = fmaxf(m1, __shfl_xor_sync(0xffffffffu, m1, o));
                }
                if (lane < 2) { sts1(mb_ + A_WM + h0 * 32 + w * 4, m0); sts1(mb_ + A_WM + h0 * 32 + 32 + w * 4, m1); }
                bar_sync(1, 256);
                float a0[4], a1[4], b0[4], b1[4];
                lds4(a0, mb_ + A_WM + h0 * 32); lds4(a1, mb_ + A_WM + h0 * 32 + 16);
                lds4(b0, mb_ + A_WM + h0 * 32 + 32); lds4(b1, mb_ + A_WM + h0 * 32 + 48);
                m0 = fmaxf(fmaxf(fmaxf(a0[0], a0[1]), fmaxf(a0[2], a0[3])), fmaxf(fmaxf(a1[0], a1[1]), fmaxf(a1[2], a1[3])));
                m1 = fmaxf(fmaxf(fmaxf(b0[0], b0[1]), fmaxf(b0[2], b0[3])), fmaxf(fmaxf(b1[0], b1[1]), fmaxf(b1[2], b1[3])));
                const uint32_t pa = mb_ + A_P + h0 * 1040 + (64 * hp + 16 * mt + grp) * 2;
                float l0 = 0.f, l1 = 0.f;
#pragma unroll
                for (int i = 0; i < 4; i++) {
                    const float e0 = ex2((sc[i][0] - m0) * L2E), e1 = ex2((sc[i][1] - m1) * L2E);
                    const float e2 = ex2((sc[i][2] - m0) * L2E), e3 = ex2((sc[i][3] - m1) * L2E);
                    if (hq < 2) {
                        sts16(pa + i * 256, e0);
                        sts16(pa + i * 256 + 1040, e1);
                        sts16(pa + i * 256 + 16, e2);
                        sts16(pa + i * 256 + 1040 + 16, e3);
                    }
                    l0 += e0 + e2; l1 += e1 + e3;
                }
#pragma unroll
                for (int o = 4; o <= 16; o <<= 1) {
                    l0 += __shfl_xor_sync(0xffffffffu, l0, o);
                    l1 += __shfl_xor_sync(0xffffffffu, l1, o);
                }
                if (lane < 2) { sts1(mb_ + A_WS + h0 * 32 + w * 4, l0); sts1(mb_ + A_WS + h0 * 32 + 32 + w * 4, l1); }
                bar_sync(1, 256);
                if (w == 7) {
                    lds4(a0, mb_ + A_WS + h0 * 32); lds4(a1, mb_ + A_WS + h0 * 32 + 16);
                    lds4(b0, mb_ + A_WS + h0 * 32 + 32); lds4(b1, mb_ + A_WS + h0 * 32 + 48);
                    l0 = ((a0[0] + a0[1]) + (a0[2] + a0[3])) + ((a1[0] + a1[1]) + (a1[2] + a1[3]));
                    l1 = ((b0[0] + b0[1]) + (b0[2] + b0[3])) + ((b1[0] + b1[1]) + (b1[2] + b1[3]));
                    if (lane < 8) {
                        const uint32_t tgt = 4 * b + (lane >> 1);
                        st_async4(mapa(mb_ + A_ST + j * 32 + (lane & 1) * 16, tgt), __float_as_uint(m0), __float_as_uint(l0),
                                  __float_as_uint(m1), __float_as_uint(l1), mapa(XBAR(1), tgt));
                    }
                }
            }
            PROF(4);
            {
                float o0[4] = {}, o1[4] = {};
                const int ch = 2 * w + (mi & 1);
                const uint32_t voff = sb + (ch >> 3) * 8192 + rr * 128 + (((ch & 7) ^ (rr & 7)) << 4);
                const uint32_t poff = mb_ + A_P + (lane & 7) * 1040 + (lane >> 3) * 16;
#pragma unroll 1
                for (int c = 0; c < 8; c++) {
                    uint32_t pf[2][4];
                    ldsm4(pf[0], poff + c * 128);
                    ldsm4(pf[1], poff + c * 128 + 64);
                    mbar_wait(FULL(s), ph);
#pragma unroll
                    for (int ks = 0; ks < 4; ks++) {
                        uint32_t a[4];
                        ldsm4t(a, voff + s * SLOT + ks * 2048);
                        if (ks & 1) mma(o1, a[0], a[1], a[2], a[3], pf[ks >> 1][2], pf[ks >> 1][3]);
                        else mma(o0, a[0], a[1], a[2], a[3], pf[ks >> 1][0], pf[ks >> 1][1]);
                    }
                    __syncwarp();
                    if (lane == 0) mbar_arrive(EMPTY(s));
                    if (++s == NSLOT) { s = 0; ph ^= 1; }
                }
                PROF(5);
                if (hq < 2) {
                    const uint32_t d = mb_ + A_OP + h0 * 544 + (16 * w + grp) * 4;
                    sts1(d, o0[0] + o1[0]);
                    sts1(d + 544, o0[1] + o1[1]);
                    sts1(d + 32, o0[2] + o1[2]);
                    sts1(d + 544 + 32, o0[3] + o1[3]);
                }
            }
            if (w < 4) {
                mbar_wait(XBAR(1), 0);
                float f[4];
                {
                    float mm[4], ll[4];
#pragma unroll
                    for (int i = 0; i < 4; i++) { mm[i] = lds1(mb_ + A_ST + i * 32 + j * 8); ll[i] = lds1(mb_ + A_ST + i * 32 + j * 8 + 4); }
                    const float M = fmaxf(fmaxf(mm[0], mm[1]), fmaxf(mm[2], mm[3]));
#pragma unroll
                    for (int i = 0; i < 4; i++) f[i] = ex2((mm[i] - M) * L2E);
                    const float inv = rcp_((ll[0] * f[0] + ll[1] * f[1]) + (ll[2] * f[2] + ll[3] * f[3]));
#pragma unroll
                    for (int i = 0; i < 4; i++) f[i] *= inv;
                }
                bar_sync(1, 256);
                const uint4 v = lds4u(mb_ + A_OP + w * 544 + lane * 16);
                const uint32_t tgt = 4 * b + w;
                st_async4(mapa(mb_ + A_RS + j * 512 + lane * 16, tgt), v.x, v.y, v.z, v.w, mapa(XBAR(2), tgt));
                const int tg2 = t >> 4, pc = t & 15;
                const uint32_t da = mapa(mb_ + A_O + b * 1040 + j * 256 + pc * 16, tg2), db = mapa(XBAR(3), tg2);
                mbar_wait(XBAR(2), 0);
                float u[4][8];
#pragma unroll
                for (int i = 0; i < 4; i++) {
                    lds4(*reinterpret_cast<float(*)[4]>(&u[i][0]), mb_ + A_RS + i * 512 + pc * 32);
                    lds4(*reinterpret_cast<float(*)[4]>(&u[i][4]), mb_ + A_RS + i * 512 + pc * 32 + 16);
                }
                float o8[8];
#pragma unroll
                for (int k = 0; k < 8; k++) o8[k] = (u[0][k] * f[0] + u[1][k] * f[1]) + (u[2][k] * f[2] + u[3][k] * f[3]);
                st_async4(da, pack2(o8[0], o8[1]), pack2(o8[2], o8[3]), pack2(o8[4], o8[5]), pack2(o8[6], o8[7]), db);
            } else {
                bar_arrive(1, 256);
            }
            const uint32_t tag = (ep + 1) & 1;
            {
                float* pub = p.attn_part + g * 1024 + r * 128 + lane * 4;
                uint32_t oa = mb_ + A_O + act_off, gp_ld = mb_ + A_GP + lane * 16;
                asm volatile("" : "+l"(pub), "+r"(oa), "+r"(gp_ld), "+r"(gp_st));
                uint32_t wf[3][4][4];
#pragma unroll
                for (int c = 0; c < 3; c++) {
                    mbar_wait(FULL(s), ph);
#pragma unroll
                    for (int k = 0; k < 4; k++) ldsm4t(wf[c][k], wt_off + s * SLOT + k * 2048);
                    if (++s == NSLOT) { s = 0; ph ^= 1; }
                }
                uint32_t wl = wt_off + s * SLOT, fl = FULL(s);
                asm volatile("" : "+r"(wl), "+r"(fl));
                mbar_wait(XBAR(3), 0);
                PROF(6);
                uint32_t bf[4][2][4];
#pragma unroll
                for (int c = 0; c < 4; c++) { ldsm4(bf[c][0], oa + c * 256); ldsm4(bf[c][1], oa + c * 256 + 64); }
                float acc[4][4] = {};
#pragma unroll
                for (int c = 0; c < 3; c++)
#pragma unroll
                    for (int k = 0; k < 4; k++)
                        mma(acc[k], wf[c][k][0], wf[c][k][1], wf[c][k][2], wf[c][k][3], bf[c][k >> 1][(k & 1) * 2], bf[c][k >> 1][(k & 1) * 2 + 1]);
                mbar_wait(fl, ph);
                PROF(9);
#pragma unroll
                for (int k = 0; k < 4; k++) {
                    uint32_t a[4];
                    ldsm4t(a, wl + k * 2048);
                    mma(acc[k], a[0], a[1], a[2], a[3], bf[3][k >> 1][(k & 1) * 2], bf[3][k >> 1][(k & 1) * 2 + 1]);
                }
                if (hq == 0) {
                    sts1(gp_st, (acc[0][0] + acc[1][0]) + (acc[2][0] + acc[3][0]));
                    sts1(gp_st + 256, (acc[0][1] + acc[1][1]) + (acc[2][1] + acc[3][1]));
                    sts1(gp_st + 32, (acc[0][2] + acc[1][2]) + (acc[2][2] + acc[3][2]));
                    sts1(gp_st + 256 + 32, (acc[0][3] + acc[1][3]) + (acc[2][3] + acc[3][3]));
                }
                if (w == 2) {
                    bar_sync(1, 256);
                    float u[4], v[4];
                    lds4(u, gp_ld); lds4(v, gp_ld + 512);
                    st_tag4(pub, u[0] + v[0], u[1] + v[1], u[2] + v[2], u[3] + v[3], tag, p.fin_n & 1);
                    PROFL(12);
                } else {
                    bar_arrive(1, 256);
                }
                PROF(7);
            }
            const uint32_t tmask = 0u - tag;
            {
                const int c0 = 16 * (cta >> 1) + 4 * (cta & 1);
                const float* src = w == 0 ? p.attn_part + grp * 1024 + (c0 >> 6) * 128 + (hq >> 1) * 64 + (c0 & 63) + (hq & 1) * 8
                                          : p.out_part + cl * 4096 + (8 * (w - 1) + grp) * 64 + r * 8 + 2 * hq;
                __nv_bfloat16* outp = p.out + c0 + hq;
                unsigned* epp = p.epoch;
                uint32_t fs = mb_ + A_RS + w * 64 + hq * 16;
                asm volatile("" : "+l"(outp), "+l"(epp), "+l"(src), "+r"(fs));
                float d4[4];
                if (w == 0) {
                    const uint4 v = poll_packet(src, tmask, p.poll_dt);
                    d4[0] = __uint_as_float(v.x); d4[1] = __uint_as_float(v.y); d4[2] = __uint_as_float(v.z); d4[3] = __uint_as_float(v.w);
                } else {
                    uint2 v;
                    int it = 0;
                    do { v = ld_poll2(src); } while (__any_sync(0xffffffffu, ((v.x ^ tmask) | (v.y ^ tmask)) & 1u) && ++it < POLL_LIMIT);
                    d4[0] = bfhi(v.x); d4[1] = bflo(v.x); d4[2] = bfhi(v.y); d4[3] = bflo(v.y);
                }
#pragma unroll
                for (int o = 4; o <= 16; o <<= 1) {
#pragma unroll
                    for (int i = 0; i < 4; i++) d4[i] += __shfl_xor_sync(0xffffffffu, d4[i], o);
                }
                if (w) {
                    if (lane < 4) sts4u(fs, __float_as_uint(d4[0]), __float_as_uint(d4[1]), __float_as_uint(d4[2]), __float_as_uint(d4[3]));
                    bar_arrive(3, 256);
                } else {
                    if (lane < 4) {
                        const uint32_t d = mb_ + A_RS + (hq & 1) * 8 + (hq >> 1) * 4;
                        sts1(d, bfr(bflo(xr.x) + bfr(d4[0])));
                        sts1(d + 16, bfr(bfhi(xr.x) + bfr(d4[1])));
                        sts1(d + 32, bfr(bflo(xr.y) + bfr(d4[2])));
                        sts1(d + 48, bfr(bfhi(xr.y) + bfr(d4[3])));
                    }
                    PROF(10);
                    bar_sync(3, 256);
                    float u[8][4];
#pragma unroll
                    for (int i = 0; i < 8; i++) lds4(u[i], fs + i * 64);
#pragma unroll
                    for (int k = 0; k < 4; k++) d4[k] = u[0][k] + bfr(((u[1][k] + u[2][k]) + (u[3][k] + u[4][k])) + ((u[5][k] + u[6][k]) + u[7][k]));
                    if (lane < 4) {
                        outp[0] = __float2bfloat16_rn(d4[0]);
                        outp[512] = __float2bfloat16_rn(d4[1]);
                        outp[8] = __float2bfloat16_rn(d4[2]);
                        outp[520] = __float2bfloat16_rn(d4[3]);
                        if (cta == 0 && lane == 0) *epp = ep + 1;
                    }
                    PROF(11);
                }
            }
            PROF_DUMP();
        }
    } else {
        const int m = cta - kAttn;
        unsigned ep;
        asm volatile("ld.relaxed.gpu.global.u32 %0, [%1];" : "=r"(ep) : "l"(p.epoch) : "memory");
        if (w == 8) {
            bar_arrive(0, kThreads);
            uint2 xv;
            asm volatile("ld.global.nc.v2.u32 {%0,%1}, [%2];" : "=r"(xv.x), "=r"(xv.y) : "l"(p.x + (lane >> 4) * 512 + 64 * r + (lane & 15) * 4));
            cluster_wait();
            if (lane == 0) {
#pragma unroll 1
                for (int i = 0; i < 6; i++) {
                    spin_until(t_start, i < p.mlp_n0 ? p.mlp_d0 + i * p.mlp_dstep : p.mlp_d1 + (i - p.mlp_n0) * p.mlp_dstep1);
                    mbar_expect(FULL(i), SLOT);
                    if (i < 4) tma2d(sb + (i & 1) * 32768 + (i >> 1) * 16384, (i & 1) ? &tm_u : &tm_g, 32 * m, 256 * (i >> 1), FULL(i));
                    else tma3d(sb + M_DOWN + (i - 4) * 16384, &tm_d, 0, 32 * m, 4 * (i - 4), FULL(i));
                }
            }
            __syncwarp();
            PROF(8);
            const uint32_t dst = mb_ + M_H + (lane >> 4) * 1040 + 128 * r + ((lane & 15) >> 1) * 16;
            uint32_t da[4], db[4], gl = mb_ + M_G3 + lane * 16;
#pragma unroll
            for (int i = 0; i < 4; i++) { da[i] = mapa(dst, 2 * i + (lane & 1)); db[i] = mapa(XBAR(3), 2 * i + (lane & 1)); }
            uint32_t sl = mb_ + M_SP + (lane >> 4) * 64;
            uint32_t sa = mapa(sl + r * 8, lane & 7), sbar = mapa(XBAR(2), lane & 7);
            float xf[4] = {bflo(xv.x), bfhi(xv.x), bflo(xv.y), bfhi(xv.y)};
            asm volatile("" : "+r"(gl), "+r"(sl), "+r"(sa), "+r"(sbar), "+f"(xf[0]), "+f"(xf[1]), "+f"(xf[2]), "+f"(xf[3]));
            bar_sync(3, 288);
            float u[8][4], a4[4];
#pragma unroll
            for (int i = 0; i < 8; i++) lds4(u[i], gl + i * 512);
#pragma unroll
            for (int k = 0; k < 4; k++) a4[k] = xf[k] + bfr(((u[0][k] + u[1][k]) + (u[2][k] + u[3][k])) + ((u[4][k] + u[5][k]) + (u[6][k] + u[7][k])));
            const uint32_t hw0 = pack2(a4[0], a4[1]), hw1 = pack2(a4[2], a4[3]);
            const uint32_t ow0 = __shfl_xor_sync(0xffffffffu, hw0, 1), ow1 = __shfl_xor_sync(0xffffffffu, hw1, 1);
            const bool odd = lane & 1;
            const uint32_t e0 = odd ? ow0 : hw0, e1 = odd ? ow1 : hw1, e2 = odd ? hw0 : ow0, e3 = odd ? hw1 : ow1;
#pragma unroll
            for (int i = 0; i < 4; i++) st_async4(da[i], e0, e1, e2, e3, db[i]);
            PROF(9);
            {
                const float h0 = bflo(hw0), h1 = bfhi(hw0), h2 = bflo(hw1), h3 = bfhi(hw1);
                float s1 = (h0 + h1) + (h2 + h3), s2 = fmaf(h0, h0, h1 * h1) + fmaf(h2, h2, h3 * h3);
#pragma unroll
                for (int o = 8; o; o >>= 1) { s1 += __shfl_xor_sync(0xffffffffu, s1, o); s2 += __shfl_xor_sync(0xffffffffu, s2, o); }
                if (!(lane & 8))
                    asm volatile("st.async.weak.shared::cluster.mbarrier::complete_tx::bytes.v2.b32 [%0], {%1,%2}, [%3];"
                                 ::"r"(sa), "r"(__float_as_uint(s1)), "r"(__float_as_uint(s2)), "r"(sbar) : "memory");
                mbar_wait(XBAR(2), 0);
                float u0[4], u1[4], u2[4], u3[4];
                lds4(u0, sl); lds4(u1, sl + 16); lds4(u2, sl + 32); lds4(u3, sl + 48);
                const float mean = (((u0[0] + u0[2]) + (u1[0] + u1[2])) + ((u2[0] + u2[2]) + (u3[0] + u3[2]))) * (1.f / 512.f);
                const float msq = (((u0[1] + u0[3]) + (u1[1] + u1[3])) + ((u2[1] + u2[3]) + (u3[1] + u3[3]))) * (1.f / 512.f);
                const float var = fmaxf(fmaf(-mean, mean, msq), 0.f);
                if ((lane & 15) == 0) sts2(mb_ + M_ST + (lane >> 4) * 8, bfr(mean), ln_rden(var));
            }
            bar_arrive(2, 288);
            PROF(10);
            PROF_DUMP();
        } else {
            bar_sync(0, kThreads);
            cluster_wait();
            const int mi = lane >> 3, rr = (lane & 7) + (mi >> 1) * 8;
            float* dout = p.out_part + w * 4096 + m * 64 + hq * 16 + 2 * grp;
            uint32_t wf[4][4][4];
            mbar_wait(FULL((w >> 2) * 2), 0);
            mbar_wait(FULL((w >> 2) * 2 + 1), 0);
#pragma unroll
            for (int tl = 0; tl < 4; tl++)
#pragma unroll
                for (int ks = 0; ks < 4; ks++) {
                    const int row = 64 * w + 16 * ks + rr;
                    const int ch = 2 * (tl & 1) + (mi & 1);
                    ldsm4t(wf[tl][ks], sb + (tl >> 1) * 32768 + row * 64 + ((ch ^ ((row >> 1) & 3)) << 4));
                }
#pragma unroll
            for (int tl = 0; tl < 4; tl++) {
                float c[4] = {};
#pragma unroll
                for (int ks = 0; ks < 4; ks++) mma(c, wf[tl][ks][0], wf[tl][ks][1], wf[tl][ks][2], wf[tl][ks][3], 0x3f803f80u, 0x3f803f80u);
                if (hq == 0) { sts1(mb_ + M_CSP + w * 256 + (tl * 16 + grp) * 4, c[0]); sts1(mb_ + M_CSP + w * 256 + (tl * 16 + grp + 8) * 4, c[2]); }
            }
            bar_sync(1, 256);
            const int bb = (w >> 1) & 1, mat = lane >> 4, col = (w & 1) * 16 + (lane & 15);
            float cs;
            {
                float f[8];
#pragma unroll
                for (int i = 0; i < 8; i++) f[i] = lds1(mb_ + M_CSP + i * 256 + (mat * 32 + col) * 4);
                cs = tree_sum(f);
            }
            uint32_t tag = (ep + 1) & 1, trnd = (ep & 1) << 16;
            uint32_t ha = mb_ + M_H + (grp & 1) * 1040 + w * 128 + hq * 4;
            uint32_t pst = mb_ + M_PART + w * 768 + ((hq >> 1) * 48 + (hq & 1) * 16 + grp) * 4;
            uint32_t pld = mb_ + M_PART + bb * 384 + (mat * 48 + col) * 4;
            uint32_t sld = mb_ + M_ST + bb * 8, hst = mb_ + M_HH + bb * 80 + col * 2, hld = mb_ + M_HH + (grp & 1) * 80 + hq * 4;
            uint32_t dn = sb + M_DOWN + w * 4096 + rr * 128 + (((mi & 1) ^ (rr & 7)) << 4), xb = XBAR(3);
            asm volatile("" : "+l"(dout), "+r"(tag), "+r"(trnd), "+r"(ha), "+r"(pst), "+r"(pld), "+r"(sld), "+r"(hst), "+r"(hld), "+r"(dn), "+r"(xb));
            PROF(0);
            {
                spin_until(t_start, p.poll_t0);
                const uint4 v = poll_packet(p.attn_part + w * 1024 + r * 128 + lane * 4, 0u - tag, p.poll_dt);
                sts4u(mb_ + M_G3 + w * 512 + lane * 16, v.x, v.y, v.z, v.w);
                bar_arrive(3, 288);
            }
            PROF(4);
            uint32_t df[4][2][4];
            if (NSLOT > 6) {
                mbar_wait(FULL(4 + (w >> 2)), 0);
#pragma unroll
                for (int tl = 0; tl < 4; tl++)
#pragma unroll
                    for (int ks = 0; ks < 2; ks++) ldsm4t(df[tl][ks], (dn ^ (tl << 5)) + ks * 2048);
            }
            mbar_wait(xb, 0);
            PROF(1);
            {
                uint32_t hf[8];
#pragma unroll
                for (int k = 0; k < 8; k++) hf[k] = lds1u(ha + k * 16);
                float c[4][4] = {};
#pragma unroll
                for (int ks = 0; ks < 4; ks++)
#pragma unroll
                    for (int tl = 0; tl < 4; tl++)
                        mma(c[tl], wf[tl][ks][0], wf[tl][ks][1], wf[tl][ks][2], wf[tl][ks][3], hf[2 * ks], hf[2 * ks + 1]);
                float v[4];
#pragma unroll
                for (int k = 0; k < 4; k++) {
                    const float lo = (hq & 1) ? c[1][k] : c[0][k], hi = (hq & 1) ? c[3][k] : c[2][k];
                    v[k] = (hq & 2) ? hi : lo;
                }
                sts1(pst, v[0]); sts1(pst + 384, v[1]); sts1(pst + 32, v[2]); sts1(pst + 384 + 32, v[3]);
            }
            if (w < 4) {
                bar_sync(2, 288);
                float f[8];
#pragma unroll
                for (int i = 0; i < 8; i++) f[i] = lds1(pld + i * 768);
                const float mean = lds1(sld), rs = lds1(sld + 4);
                const float v = bfr(fmaf(-mean, cs, tree_sum(f)) * rs);
                const float u = __shfl_xor_sync(0xffffffffu, v, 16);
                const float e = ex2(v * fmaf(v * v, -0.10294324f, -2.3022082f));
                const float ge = bfr(v * rcp_(1.f + e));
                if (lane < 16) sts16(hst, ge * u);
                PROF(2);
            } else {
                bar_arrive(2, 288);
            }
            if (NSLOT <= 6) {
                mbar_wait(FULL(4 + (w >> 2)), 0);
#pragma unroll
                for (int tl = 0; tl < 4; tl++)
#pragma unroll
                    for (int ks = 0; ks < 2; ks++) ldsm4t(df[tl][ks], (dn ^ (tl << 5)) + ks * 2048);
            }
            bar_sync(1, 256);
            uint32_t hf[4];
#pragma unroll
            for (int k = 0; k < 4; k++) hf[k] = lds1u(hld + k * 16);
            float c[4][4] = {};
#pragma unroll
            for (int ks = 0; ks < 2; ks++)
#pragma unroll
                for (int tl = 0; tl < 4; tl++) mma(c[tl], df[tl][ks][0], df[tl][ks][1], df[tl][ks][2], df[tl][ks][3], hf[2 * ks], hf[2 * ks + 1]);
            {
                float v[4];
#pragma unroll
                for (int k = 0; k < 4; k++) {
                    const float lo = (hq & 1) ? c[1][k] : c[0][k], hi = (hq & 1) ? c[3][k] : c[2][k];
                    v[k] = (hq & 2) ? hi : lo;
                }
                st_mail2(dout, pack_tag(v[0], v[1], tag, trnd), pack_tag(v[2], v[3], tag, trnd));
            }
            PROF(3);
            PROF_DUMP();
        }
    }
}

typedef CUresult (*EncodeFn)(CUtensorMap*, CUtensorMapDataType, cuuint32_t, void*, const cuuint64_t*, const cuuint64_t*,
                             const cuuint32_t*, const cuuint32_t*, CUtensorMapInterleave, CUtensorMapSwizzle,
                             CUtensorMapL2promotion, CUtensorMapFloatOOBfill);

void make_map(EncodeFn enc, CUtensorMap* m, const void* ptr, int rank, const cuuint64_t* dims, const cuuint64_t* strides,
              const cuuint32_t* box, CUtensorMapSwizzle sw) {
    const cuuint32_t es[3] = {1, 1, 1};
    enc(m, CU_TENSOR_MAP_DATA_TYPE_BFLOAT16, rank, const_cast<void*>(ptr), dims, strides, box, es, CU_TENSOR_MAP_INTERLEAVE_NONE, sw,
        CU_TENSOR_MAP_L2_PROMOTION_L2_128B, CU_TENSOR_MAP_FLOAT_OOB_FILL_NONE);
}

}

int g_mlp_d0 = 10000, g_mlp_dstep = 1500, g_first_pass = 0, g_depth = 10, g_small = -1, g_mlp_n0 = 4, g_mlp_d1 = 17000, g_mlp_dstep1 = 100;
int g_poll_n = 2, g_poll_t0 = 17000, g_poll_dt = 0, g_fin_n = 1, g_fin_t0 = 0;

extern "C" void kernel_launch(void* const* d_in, const int* in_sizes, int n_in, void* d_out, int out_size) {
    (void)in_sizes; (void)n_in; (void)out_size;
    static EncodeFn enc = nullptr;
    static void *a_epoch, *a_mail;
    if (!enc) {
        void* fn = nullptr;
        cudaDriverEntryPointQueryResult qr;
        cudaGetDriverEntryPoint("cuTensorMapEncodeTiled", &fn, cudaEnableDefault, &qr);
        enc = (EncodeFn)fn;
        cudaFuncSetAttribute(fused_decode<kBig>, cudaFuncAttributeMaxDynamicSharedMemorySize, smem_bytes(kBig));
        cudaFuncSetAttribute(fused_decode<kSmall>, cudaFuncAttributeMaxDynamicSharedMemorySize, smem_bytes(kSmall));
        cudaGetSymbolAddress(&a_epoch, g_epoch);
        cudaGetSymbolAddress(&a_mail, g_mail);
    }
    CUtensorMap tq, tk, tv, to, tg, tu, td;
    {
        const cuuint64_t d[2] = {4096, 512}, s[1] = {8192}; const cuuint32_t bx[2] = {64, 128};
        make_map(enc, &tq, d_in[3], 2, d, s, bx, CU_TENSOR_MAP_SWIZZLE_128B);
    }
    {
        const cuuint64_t d[3] = {64, 131072, 2}, s[2] = {256, 128}; const cuuint32_t bx[3] = {64, 64, 2};
        make_map(enc, &tk, d_in[1], 3, d, s, bx, CU_TENSOR_MAP_SWIZZLE_128B);
        make_map(enc, &tv, d_in[2], 3, d, s, bx, CU_TENSOR_MAP_SWIZZLE_128B);
    }
    {
        const cuuint64_t d[2] = {512, 4096}, s[1] = {1024}; const cuuint32_t bx[2] = {64, 128};
        make_map(enc, &to, d_in[4], 2, d, s, bx, CU_TENSOR_MAP_SWIZZLE_128B);
    }
    {
        const cuuint64_t d[2] = {1792, 512}, s[1] = {3584}; const cuuint32_t bx[2] = {32, 256};
        make_map(enc, &tg, d_in[6], 2, d, s, bx, CU_TENSOR_MAP_SWIZZLE_64B);
        make_map(enc, &tu, d_in[7], 2, d, s, bx, CU_TENSOR_MAP_SWIZZLE_64B);
    }
    {
        const cuuint64_t d[3] = {64, 1792, 8}, s[2] = {1024, 128}; const cuuint32_t bx[3] = {64, 32, 4};
        make_map(enc, &td, d_in[8], 3, d, s, bx, CU_TENSOR_MAP_SWIZZLE_128B);
    }
    Params p;
    p.x = (const __nv_bfloat16*)d_in[0];
    p.out = (__nv_bfloat16*)d_out;
    p.epoch = (unsigned*)a_epoch;
    p.attn_part = (float*)a_mail;
    p.out_part = p.attn_part + 8 * 1024;
    p.mlp_d0 = g_mlp_d0;
    p.mlp_dstep = g_mlp_dstep;
    p.first_pass = g_first_pass;
    p.depth = g_depth;
    p.poll_n = g_poll_n; p.poll_t0 = g_poll_t0; p.poll_dt = g_poll_dt; p.fin_n = g_fin_n; p.fin_t0 = g_fin_t0;
    p.mlp_n0 = g_mlp_n0; p.mlp_d1 = g_mlp_d1; p.mlp_dstep1 = g_mlp_dstep1;
    cudaLaunchConfig_t cfg = {};
    cfg.gridDim = dim3(kCtas);
    cfg.stream = cudaStreamPerThread;
    cudaLaunchAttribute at[1];
    at[0].id = cudaLaunchAttributeClusterDimension;
    at[0].val.clusterDim.x = 8; at[0].val.clusterDim.y = 1; at[0].val.clusterDim.z = 1;
    cfg.attrs = at;
    cfg.numAttrs = 1;
    if (g_small < 0) {
        int n = 0;
        cfg.dynamicSmemBytes = smem_bytes(kBig);
        cfg.blockDim = dim3(threads(kBig));
        cudaError_t e = cudaOccupancyMaxActiveClusters(&n, fused_decode<kBig>, &cfg);
        g_small = (e != cudaSuccess || n < kCtas / 8) ? 1 : 0;
        (void)cudaGetLastError();
    }
    if (g_small) {
        cfg.dynamicSmemBytes = smem_bytes(kSmall);
        cfg.blockDim = dim3(threads(kSmall));
        if (p.depth > kSmall - 1) p.depth = kSmall - 1;
        cudaLaunchKernelEx(&cfg, fused_decode<kSmall>, tq, tk, tv, to, tg, tu, td, p);
    } else {
        cfg.dynamicSmemBytes = smem_bytes(kBig);
        cfg.blockDim = dim3(threads(kBig));
        cudaLaunchKernelEx(&cfg, fused_decode<kBig>, tq, tk, tv, to, tg, tu, td, p);
    }
}
```

```cpp
#include <cuda_runtime.h>
#include <cuda_bf16.h>
#include <cuda.h>
#include <stdint.h>

namespace {

constexpr int kAttn = 64, kMlp = 56, kCtas = kAttn + kMlp;
constexpr int SLOT = 16384;
constexpr int kBig = 13, kSmall = 6;
constexpr int A_XN = 0;
constexpr int A_O = A_XN + 2080;
constexpr int A_Q = A_O + 2080;
constexpr int A_P = A_Q + 1088;
constexpr int A_RS = A_P + 4160;
constexpr int A_OP = A_RS + 2048;
constexpr int A_ST = A_OP + 2176;
constexpr int A_WM = A_ST + 128;
constexpr int A_WS = A_WM + 128;
constexpr int A_GP = A_WS + 128;
constexpr int A_END = A_GP + 1024;
constexpr int M_DOWN = 65536;
constexpr int M_H = 0;
constexpr int M_PART = M_H + 2080;
constexpr int M_CSP = M_PART + 6144;
constexpr int M_CS = M_CSP + 2048;
constexpr int M_HH = M_CS + 256;
constexpr int M_ST = M_HH + 160;
constexpr int M_G3 = M_ST + 16;
constexpr int M_SP = M_G3 + 4096;
constexpr int M_END = M_SP + 128;
constexpr int OFF_BAR = ((A_END > M_END ? A_END : M_END) + 15) / 16 * 16;
constexpr int OFF_PROF = OFF_BAR + 36 * 8;
constexpr int MISC_BYTES = OFF_PROF + 64;
constexpr int kThreads = 320;
constexpr int smem_bytes(int nslot) { return nslot * SLOT + MISC_BYTES + 1024; }

constexpr int POLL_LIMIT = 200000;
constexpr int MBAR_LIMIT = 20000000;
constexpr int SPIN_LIMIT = 2000000;

struct Params {
    const __nv_bfloat16* x;
    __nv_bfloat16* out;
    unsigned* epoch;
    float* attn_part;
    float* out_part;
    int pace, lead, mlp_t0, mlp_dt, poll_t0;
};

__device__ unsigned g_epoch;
__device__ __align__(1024) float g_mail[(8 + 32) * 1024];
#define PROF(i) do {} while (0)
#define PROF_DUMP() do {} while (0)
#define PROFL(i) do {} while (0)
__device__ __forceinline__ uint32_t clock32() { uint32_t c; asm volatile("mov.u32 %0, %%clock;" : "=r"(c) :: "memory"); return c; }

__device__ __forceinline__ uint32_t nsclock() { uint32_t c; asm volatile("mov.u32 %0, %%globaltimer_lo;" : "=r"(c) :: "memory"); return c; }
__device__ __forceinline__ uint32_t s2u(const void* p) { return (uint32_t)__cvta_generic_to_shared(p); }
__device__ __forceinline__ void mbar_init(uint32_t a, int c) { asm volatile("mbarrier.init.shared::cta.b64 [%0], %1;" ::"r"(a), "r"(c) : "memory"); }
__device__ __forceinline__ void mbar_expect(uint32_t a, uint32_t b) { asm volatile("mbarrier.arrive.expect_tx.shared::cta.b64 _, [%0], %1;" ::"r"(a), "r"(b) : "memory"); }
__device__ __forceinline__ void mbar_arrive(uint32_t a) { asm volatile("mbarrier.arrive.shared::cta.b64 _, [%0];" ::"r"(a) : "memory"); }
__device__ __forceinline__ void mbar_wait(uint32_t a, uint32_t ph) {
    uint32_t ok; int it = 0;
    do {
        asm volatile("{ .reg .pred p; mbarrier.try_wait.parity.shared::cta.b64 p, [%1], %2; selp.u32 %0, 1, 0, p; }" : "=r"(ok) : "r"(a), "r"(ph) : "memory");
    } while (!ok && ++it < MBAR_LIMIT);
}
__device__ __forceinline__ bool mbar_test(uint32_t a, uint32_t ph) {
    uint32_t ok;
    asm volatile("{ .reg .pred p; mbarrier.test_wait.parity.shared::cta.b64 p, [%1], %2; selp.u32 %0, 1, 0, p; }" : "=r"(ok) : "r"(a), "r"(ph) : "memory");
    return ok;
}
__device__ __forceinline__ void tma2d(uint32_t dst, const CUtensorMap* m, int c0, int c1, uint32_t bar) {
    asm volatile("cp.async.bulk.tensor.2d.shared::cluster.global.mbarrier::complete_tx::bytes [%0], [%1, {%3, %4}], [%2];"
                 ::"r"(dst), "l"(m), "r"(bar), "r"(c0), "r"(c1) : "memory");
}
__device__ __forceinline__ void tma3d(uint32_t dst, const CUtensorMap* m, int c0, int c1, int c2, uint32_t bar) {
    asm volatile("cp.async.bulk.tensor.3d.shared::cluster.global.mbarrier::complete_tx::bytes [%0], [%1, {%3, %4, %5}], [%2];"
                 ::"r"(dst), "l"(m), "r"(bar), "r"(c0), "r"(c1), "r"(c2) : "memory");
}
__device__ __forceinline__ uint32_t mapa(uint32_t a, uint32_t rank) { uint32_t r; asm("mapa.shared::cluster.u32 %0, %1, %2;" : "=r"(r) : "r"(a), "r"(rank)); return r; }
__device__ __forceinline__ void st_async4(uint32_t dst, uint32_t a, uint32_t b, uint32_t c, uint32_t d, uint32_t bar) {
    asm volatile("st.async.weak.shared::cluster.mbarrier::complete_tx::bytes.v4.b32 [%0], {%1,%2,%3,%4}, [%5];"
                 ::"r"(dst), "r"(a), "r"(b), "r"(c), "r"(d), "r"(bar) : "memory");
}
__device__ __forceinline__ void ldsm4(uint32_t (&r)[4], uint32_t a) {
    asm volatile("ldmatrix.sync.aligned.m8n8.x4.shared.b16 {%0,%1,%2,%3}, [%4];" : "=r"(r[0]), "=r"(r[1]), "=r"(r[2]), "=r"(r[3]) : "r"(a) : "memory");
}
__device__ __forceinline__ void ldsm4t(uint32_t (&r)[4], uint32_t a) {
    asm volatile("ldmatrix.sync.aligned.m8n8.x4.trans.shared.b16 {%0,%1,%2,%3}, [%4];" : "=r"(r[0]), "=r"(r[1]), "=r"(r[2]), "=r"(r[3]) : "r"(a) : "memory");
}
__device__ __forceinline__ void mma(float (&c)[4], uint32_t a0, uint32_t a1, uint32_t a2, uint32_t a3, uint32_t b0, uint32_t b1) {
    asm volatile("mma.sync.aligned.m16n8k16.row.col.f32.bf16.bf16.f32 {%0,%1,%2,%3}, {%4,%5,%6,%7}, {%8,%9}, {%0,%1,%2,%3};"
                 : "+f"(c[0]), "+f"(c[1]), "+f"(c[2]), "+f"(c[3]) : "r"(a0), "r"(a1), "r"(a2), "r"(a3), "r"(b0), "r"(b1));
}
__device__ __forceinline__ void bar_sync(int id, int n) { asm volatile("bar.sync %0, %1;" ::"r"(id), "r"(n) : "memory"); }
__device__ __forceinline__ void bar_arrive(int id, int n) { asm volatile("bar.arrive %0, %1;" ::"r"(id), "r"(n) : "memory"); }
__device__ __forceinline__ void cluster_arrive() { asm volatile("barrier.cluster.arrive.relaxed.aligned;" ::: "memory"); }
__device__ __forceinline__ void cluster_wait() { asm volatile("barrier.cluster.wait.acquire.aligned;" ::: "memory"); }
__device__ __forceinline__ uint32_t pack2(float lo, float hi) { uint32_t r; asm("cvt.rn.bf16x2.f32 %0, %1, %2;" : "=r"(r) : "f"(hi), "f"(lo)); return r; }
__device__ __forceinline__ float bfr(float v) { return __uint_as_float(pack2(0.f, v)); }
__device__ __forceinline__ float bflo(uint32_t v) { return __uint_as_float(v << 16); }
__device__ __forceinline__ float bfhi(uint32_t v) { return __uint_as_float(v & 0xffff0000u); }
__device__ __forceinline__ float ex2(float v) { float r; asm("ex2.approx.ftz.f32 %0, %1;" : "=f"(r) : "f"(v)); return r; }
__device__ __forceinline__ uint4 ld_poll(const float* p) {
    uint4 v;
    asm volatile("ld.relaxed.gpu.global.v4.u32 {%0,%1,%2,%3}, [%4];" : "=r"(v.x), "=r"(v.y), "=r"(v.z), "=r"(v.w) : "l"(p) : "memory");
    return v;
}
__device__ __forceinline__ void st_mail4(float* p, uint32_t v) {
    asm volatile("st.relaxed.gpu.global.v4.u32 [%0], {%1,%1,%1,%1};" ::"l"(p), "r"(v) : "memory");
}
__device__ __forceinline__ void exch_tag4(float* p, float a, float b, float c, float d, uint32_t tag) {
    const uint32_t x = (__float_as_uint(a) & ~1u) | tag, y = (__float_as_uint(b) & ~1u) | tag;
    const uint32_t z = (__float_as_uint(c) & ~1u) | tag, u = (__float_as_uint(d) & ~1u) | tag;
    asm volatile("{ .reg .b128 t, o; mov.b128 t, {%1, %2}; atom.relaxed.gpu.global.exch.b128 o, [%0], t; }" ::"l"(p),
                 "l"((unsigned long long)x | ((unsigned long long)y << 32)), "l"((unsigned long long)z | ((unsigned long long)u << 32)) : "memory");
}
__device__ __forceinline__ uint32_t pack_tag(float hi, float lo, uint32_t tag, uint32_t trnd) {
    return pack2(0.f, hi) | (((__float_as_uint(lo) + trnd) >> 17) << 1) | tag;
}
__device__ __forceinline__ void st_mail2(float* p, uint32_t x, uint32_t y) {
    asm volatile("st.relaxed.gpu.global.v2.u32 [%0], {%1,%2};" ::"l"(p), "r"(x), "r"(y) : "memory");
}
__device__ __forceinline__ uint2 ld_poll2(const float* p) {
    uint2 v;
    asm volatile("ld.relaxed.gpu.global.v2.u32 {%0,%1}, [%2];" : "=r"(v.x), "=r"(v.y) : "l"(p) : "memory");
    return v;
}
__device__ __forceinline__ void lds4(float (&v)[4], uint32_t a) {
    asm volatile("ld.shared.v4.f32 {%0,%1,%2,%3}, [%4];" : "=f"(v[0]), "=f"(v[1]), "=f"(v[2]), "=f"(v[3]) : "r"(a) : "memory");
}
__device__ __forceinline__ uint4 lds4u(uint32_t a) {
    uint4 v; asm volatile("ld.shared.v4.u32 {%0,%1,%2,%3}, [%4];" : "=r"(v.x), "=r"(v.y), "=r"(v.z), "=r"(v.w) : "r"(a) : "memory"); return v;
}
__device__ __forceinline__ float lds1(uint32_t a) { float v; asm volatile("ld.shared.f32 %0, [%1];" : "=f"(v) : "r"(a) : "memory"); return v; }
__device__ __forceinline__ uint32_t lds1u(uint32_t a) { uint32_t v; asm volatile("ld.shared.u32 %0, [%1];" : "=r"(v) : "r"(a) : "memory"); return v; }
__device__ __forceinline__ void sts1(uint32_t a, float v) { asm volatile("st.shared.f32 [%0], %1;" ::"r"(a), "f"(v) : "memory"); }
__device__ __forceinline__ void sts2(uint32_t a, float v, float w) { asm volatile("st.shared.v2.f32 [%0], {%1,%2};" ::"r"(a), "f"(v), "f"(w) : "memory"); }
__device__ __forceinline__ void sts16(uint32_t a, float v) {
    asm volatile("{ .reg .b16 lo, hi; mov.b32 {lo, hi}, %1; st.shared.u16 [%0], lo; }" ::"r"(a), "r"(pack2(v, 0.f)) : "memory");
}
__device__ __forceinline__ void sts4u(uint32_t a, uint32_t x, uint32_t y, uint32_t z, uint32_t w) {
    asm volatile("st.shared.v4.u32 [%0], {%1,%2,%3,%4};" ::"r"(a), "r"(x), "r"(y), "r"(z), "r"(w) : "memory");
}

template <int N>
__device__ __forceinline__ float tree_sum(float (&f)[N]) {
#pragma unroll
    for (int d = 1; d < N; d <<= 1)
#pragma unroll
        for (int i = 0; i + d < N; i += 2 * d) f[i] += f[i + d];
    return f[0];
}
__device__ __forceinline__ void spin_until(uint32_t due) {
    int it = 0;
    while ((int)(nsclock() - due) < 0 && ++it < SPIN_LIMIT) {}
}
__device__ __forceinline__ uint4 poll_packet(const float* src, uint32_t tmask) {
    uint4 v;
    int it = 0;
    do {
        v = ld_poll(src);
    } while (__any_sync(0xffffffffu, (((v.x ^ tmask) | (v.y ^ tmask)) | ((v.z ^ tmask) | (v.w ^ tmask))) & 1u) && ++it < POLL_LIMIT);
    return v;
}

__device__ __forceinline__ float rcp_(float v) { float r; asm("rcp.approx.ftz.f32 %0, %1;" : "=f"(r) : "f"(v)); return r; }
__device__ __forceinline__ float sqrt_(float v) { float r; asm("sqrt.approx.ftz.f32 %0, %1;" : "=f"(r) : "f"(v)); return r; }
__device__ __forceinline__ float ln_rden(float var) { return rcp_(bfr(sqrt_(bfr(bfr(var) + 1e-5f)))); }

template <int NSLOT>
__global__ void __launch_bounds__(kThreads, NSLOT <= 6 ? 2 : 1)
fused_decode(const __grid_constant__ CUtensorMap tm_wq, const __grid_constant__ CUtensorMap tm_k,
             const __grid_constant__ CUtensorMap tm_v, const __grid_constant__ CUtensorMap tm_wo,
             const __grid_constant__ CUtensorMap tm_g, const __grid_constant__ CUtensorMap tm_u,
             const __grid_constant__ CUtensorMap tm_d, const Params p) {
    extern __shared__ uint8_t smem_raw[];
    const uint32_t sb = (s2u(smem_raw) + 1023u) & ~1023u;
    const uint32_t mb_ = sb + NSLOT * SLOT;
    const int t = threadIdx.x, w = t >> 5, lane = t & 31, grp = lane >> 2, hq = lane & 3;
    const int cta = blockIdx.x, r = cta & 7, cl = cta >> 3;
    const uint32_t bar0 = mb_ + OFF_BAR;
    const uint32_t ns0 = nsclock();
#define FULL(s) (bar0 + 8 * (s))
#define EMPTY(s) (bar0 + 128 + 8 * (s))
#define XBAR(i) (bar0 + 256 + 8 * (i))
#define MFULL(i) ((i) < 6 ? FULL(i) : EMPTY((i) - 6))
    if (w == 8) {
        if (lane == 0) {
            mbar_init(FULL(0), 1);
            asm volatile("fence.mbarrier_init.release.cluster;" ::: "memory");
            if (cta < kAttn) { mbar_expect(FULL(0), SLOT); tma3d(sb, &tm_wq, 64 * cta, 0, 0, FULL(0)); }
#pragma unroll
            for (int s = 1; s < NSLOT; s++) mbar_init(FULL(s), 1);
#pragma unroll
            for (int s = 0; s < NSLOT; s++) mbar_init(EMPTY(s), cta < kAttn ? 8 : 1);
            asm volatile("fence.mbarrier_init.release.cluster;" ::: "memory");
        }
        __syncwarp();
        if (cta < kAttn) { if (lane >= 1 && lane < NSLOT) mbar_expect(FULL(lane), SLOT); }
        else if (lane < 10) mbar_expect(MFULL(lane), lane < 8 ? SLOT / 2 : SLOT);
    }
    if (t == 64) {
#pragma unroll
        for (int i = 0; i < 4; i++) mbar_init(XBAR(i), 1);
        asm volatile("fence.mbarrier_init.release.cluster;" ::: "memory");
        mbar_expect(XBAR(0), 1024);
        mbar_expect(XBAR(1), 128);
        mbar_expect(XBAR(2), cta < kAttn ? 2048 : 128);
        mbar_expect(XBAR(3), 2048);
    }
    __syncwarp();
    cluster_arrive();

    if (cta < kAttn) {
        const int g = cl, b = r >> 2, j = r & 3;
        if (w == 9) {
            bar_arrive(0, kThreads);
        } else if (w == 8) {
            bar_arrive(0, kThreads);
            if (lane == 0) {
                const int kvrow = (b * 8 + g) * 8192 + 6144 + 512 * j;
                uint32_t dst = sb + SLOT, fb = FULL(1), fend = FULL(NSLOT), ph = 1;
                asm volatile("" : "+r"(dst), "+r"(fb), "+r"(fend));
                int i = 1;
                const uint32_t pace = p.pace;
                uint32_t due = ns0 - p.lead;
                auto run = [&](const CUtensorMap* m, int c0, int c1, int step, int n) {
#pragma unroll 1
                    for (; n > 0; n--, i++, c1 += step) {
                        if (i >= NSLOT) { mbar_wait(fb + 128, ph); mbar_expect(fb, SLOT); }
                        due += pace;
                        spin_until(due);
                        tma3d(dst, m, c0, c1, 0, fb);
                        dst += SLOT; fb += 8;
                        if (fb == fend) { fb -= 8 * NSLOT; dst -= SLOT * NSLOT; ph ^= 1; }
                    }
                };
                run(&tm_wq, 64 * cta, 128, 128, 3);
                run(&tm_k, 0, kvrow, 64, 8);
                run(&tm_v, 0, kvrow, 64, 8);
                run(&tm_wo, 64 * r, 512 * g, 128, 4);
                PROF(8);
                PROF_DUMP();
            }
            __syncwarp();
            cluster_wait();
        } else {
            if (w < 2) {
                const uint4* xp = reinterpret_cast<const uint4*>(p.x + w * 512 + lane * 16);
                const uint4 xa = __ldg(xp), xb = __ldg(xp + 1);
                const uint32_t u[8] = {xa.x, xa.y, xa.z, xa.w, xb.x, xb.y, xb.z, xb.w};
                float v[16], f[16];
#pragma unroll
                for (int i = 0; i < 8; i++) { v[2 * i] = bflo(u[i]); v[2 * i + 1] = bfhi(u[i]); }
#pragma unroll
                for (int i = 0; i < 16; i++) f[i] = v[i];
                float sm = tree_sum(f);
#pragma unroll
                for (int o = 16; o; o >>= 1) sm += __shfl_xor_sync(0xffffffffu, sm, o);
                const float mean = sm * (1.f / 512.f);
#pragma unroll
                for (int i = 0; i < 16; i++) { const float d = v[i] - mean; f[i] = d * d; }
                float sq = tree_sum(f);
#pragma unroll
                for (int o = 16; o; o >>= 1) sq += __shfl_xor_sync(0xffffffffu, sq, o);
                const float mb = bfr(mean), rden = ln_rden(sq * (1.f / 512.f));
                uint32_t o[8];
#pragma unroll
                for (int i = 0; i < 8; i++) {
                    const uint32_t c = pack2(v[2 * i] - mb, v[2 * i + 1] - mb);
                    o[i] = pack2(bflo(c) * rden, bfhi(c) * rden);
                }
                const uint32_t d = mb_ + A_XN + w * 1040 + lane * 32;
                sts4u(d, o[0], o[1], o[2], o[3]);
                sts4u(d + 16, o[4], o[5], o[6], o[7]);
            }
            unsigned ep;
            asm volatile("ld.relaxed.gpu.global.u32 %0, [%1];" : "=r"(ep) : "l"(p.epoch) : "memory");
            uint2 xr;
            asm volatile("ld.global.nc.v2.u32 {%0,%1}, [%2];" : "=r"(xr.x), "=r"(xr.y) : "l"(p.x + (hq >> 1) * 512 + 16 * (cta >> 1) + 4 * (cta & 1) + (hq & 1) * 8));
            const int mt = w & 3, hp = w >> 2, h0 = 2 * (hq & 1);
            const int mi = lane >> 3, rr = (lane & 7) + (mi >> 1) * 8;
            const uint32_t act_off = (lane & 7) * 1040 + hp * 128 + mi * 16;
            const uint32_t wt_off = sb + (64 * hp + rr) * 128 + (((2 * mt + (mi & 1)) ^ (rr & 7)) << 4);
            uint32_t gp_st = mb_ + A_GP + hp * 512 + (16 * mt + grp) * 4;
            constexpr float L2E = 1.4426950408889634f;
            bar_sync(0, kThreads);
            PROF(0);
            {
                float acc[2][4] = {};
#pragma unroll 1
                for (int i = 0; i < 4; i++) {
                    uint32_t bf[2][4];
                    ldsm4(bf[0], mb_ + A_XN + act_off + i * 256);
                    ldsm4(bf[1], mb_ + A_XN + act_off + i * 256 + 64);
                    mbar_wait(FULL(i), 0);
                    if (i == 3) PROF(2);
#pragma unroll
                    for (int k = 0; k < 4; k++) {
                        uint32_t a[4];
                        ldsm4t(a, wt_off + i * SLOT + k * 2048);
                        mma(acc[k & 1], a[0], a[1], a[2], a[3], bf[k >> 1][(k & 1) * 2], bf[k >> 1][(k & 1) * 2 + 1]);
                    }
                    __syncwarp();
                    if (lane == 0) mbar_arrive(EMPTY(i));
                }
                if (hq == 0) {
                    sts1(gp_st, acc[0][0] + acc[1][0]); sts1(gp_st + 256, acc[0][1] + acc[1][1]);
                    sts1(gp_st + 32, acc[0][2] + acc[1][2]); sts1(gp_st + 256 + 32, acc[0][3] + acc[1][3]);
                }
                cluster_wait();
                bar_sync(1, 256);
                if (w < 2) {
                    const int tg = t >> 3, pc = t & 7;
                    const uint32_t src = mb_ + A_GP + (tg >> 2) * 256 + pc * 32;
                    float u0[4], u1[4], v0[4], v1[4];
                    lds4(u0, src); lds4(u1, src + 16); lds4(v0, src + 512); lds4(v1, src + 512 + 16);
                    st_async4(mapa(mb_ + A_Q + (r >> 1) * 272 + (r & 1) * 128 + pc * 16, tg), pack2(u0[0] + v0[0], u0[1] + v0[1]),
                              pack2(u0[2] + v0[2], u0[3] + v0[3]), pack2(u1[0] + v1[0], u1[1] + v1[1]), pack2(u1[2] + v1[2], u1[3] + v1[3]),
                              mapa(XBAR(0), tg));
                }
            }
            if (w == 2) st_mail4(p.attn_part + g * 1024 + r * 128 + lane * 4, ep & 1);
            PROF(1);
            int s = 4, ph = 0;
            float sc[4][4] = {};
            {
                mbar_wait(XBAR(0), 0);
                uint32_t qf[4][4];
#pragma unroll
                for (int i = 0; i < 4; i++) ldsm4(qf[i], mb_ + A_Q + (lane & 7) * 272 + i * 64 + (lane >> 3) * 16);
                const int row = 16 * mt + (lane & 7) + ((lane >> 3) & 1) * 8;
                const uint32_t x0a = row * 128 + ((((lane >> 4) ^ (row & 7))) << 4);
#pragma unroll 1
                for (int c = 0; c < 8; c++) {
                    if ((c & 1) == hp) {
                        mbar_wait(FULL(s), ph);
                        float s0[4] = {}, s1[4] = {};
                        const uint32_t kb = sb + s * SLOT;
#pragma unroll
                        for (int ks = 0; ks < 8; ks++) {
                            uint32_t a[4];
                            ldsm4(a, kb + (ks >> 2) * 8192 + (x0a ^ ((ks & 3) << 5)));
                            if (ks & 1) mma(s1, a[0], a[1], a[2], a[3], qf[ks >> 1][2], qf[ks >> 1][3]);
                            else mma(s0, a[0], a[1], a[2], a[3], qf[ks >> 1][0], qf[ks >> 1][1]);
                        }
#pragma unroll
                        for (int k = 0; k < 3; k++)
#pragma unroll
                            for (int e = 0; e < 4; e++) sc[k][e] = sc[k + 1][e];
                        const uint32_t r1 = pack2(s0[0] + s1[0], s0[1] + s1[1]), r3 = pack2(s0[2] + s1[2], s0[3] + s1[3]);
                        const uint32_t r2 = pack2(bflo(r1) * 0.08838834764831845f, bfhi(r1) * 0.08838834764831845f);
                        const uint32_t r4 = pack2(bflo(r3) * 0.08838834764831845f, bfhi(r3) * 0.08838834764831845f);
                        sc[3][0] = bflo(r2); sc[3][1] = bfhi(r2); sc[3][2] = bflo(r4); sc[3][3] = bfhi(r4);
                        __syncwarp();
                        if (lane < 2) mbar_arrive(EMPTY(s));
                    }
                    if (++s == NSLOT) { s = 0; ph ^= 1; }
                }
            }
            PROF(3);
            {
                float m0 = fmaxf(fmaxf(fmaxf(sc[0][0], sc[1][0]), fmaxf(sc[2][0], sc[3][0])), fmaxf(fmaxf(sc[0][2], sc[1][2]), fmaxf(sc[2][2], sc[3][2])));
                float m1 = fmaxf(fmaxf(fmaxf(sc[0][1], sc[1][1]), fmaxf(sc[2][1], sc[3][1])), fmaxf(fmaxf(sc[0][3], sc[1][3]), fmaxf(sc[2][3], sc[3][3])));
#pragma unroll
                for (int o = 4; o <= 16; o <<= 1) {
                    m0 = fmaxf(m0, __shfl_xor_sync(0xffffffffu, m0, o));
                    m1 = fmaxf(m1, __shfl_xor_sync(0xffffffffu, m1, o));
                }
                if (lane < 2) { sts1(mb_ + A_WM + h0 * 32 + w * 4, m0); sts1(mb_ + A_WM + h0 * 32 + 32 + w * 4, m1); }
                bar_sync(1, 256);
                float a0[4], a1[4], b0[4], b1[4];
                lds4(a0, mb_ + A_WM + h0 * 32); lds4(a1, mb_ + A_WM + h0 * 32 + 16);
                lds4(b0, mb_ + A_WM + h0 * 32 + 32); lds4(b1, mb_ + A_WM + h0 * 32 + 48);
                m0 = fmaxf(fmaxf(fmaxf(a0[0], a0[1]), fmaxf(a0[2], a0[3])), fmaxf(fmaxf(a1[0], a1[1]), fmaxf(a1[2], a1[3])));
                m1 = fmaxf(fmaxf(fmaxf(b0[0], b0[1]), fmaxf(b0[2], b0[3])), fmaxf(fmaxf(b1[0], b1[1]), fmaxf(b1[2], b1[3])));
                const uint32_t pa = mb_ + A_P + h0 * 1040 + (64 * hp + 16 * mt + grp) * 2;
                float l0 = 0.f, l1 = 0.f;
#pragma unroll
                for (int i = 0; i < 4; i++) {
                    const float e0 = ex2((sc[i][0] - m0) * L2E), e1 = ex2((sc[i][1] - m1) * L2E);
                    const float e2 = ex2((sc[i][2] - m0) * L2E), e3 = ex2((sc[i][3] - m1) * L2E);
                    if (hq < 2) {
                        sts16(pa + i * 256, e0);
                        sts16(pa + i * 256 + 1040, e1);
                        sts16(pa + i * 256 + 16, e2);
                        sts16(pa + i * 256 + 1040 + 16, e3);
                    }
                    l0 += e0 + e2; l1 += e1 + e3;
                }
#pragma unroll
                for (int o = 4; o <= 16; o <<= 1) {
                    l0 += __shfl_xor_sync(0xffffffffu, l0, o);
                    l1 += __shfl_xor_sync(0xffffffffu, l1, o);
                }
                if (lane < 2) { sts1(mb_ + A_WS + h0 * 32 + w * 4, l0); sts1(mb_ + A_WS + h0 * 32 + 32 + w * 4, l1); }
                bar_sync(1, 256);
                if (w == 7) {
                    lds4(a0, mb_ + A_WS + h0 * 32); lds4(a1, mb_ + A_WS + h0 * 32 + 16);
                    lds4(b0, mb_ + A_WS + h0 * 32 + 32); lds4(b1, mb_ + A_WS + h0 * 32 + 48);
                    l0 = ((a0[0] + a0[1]) + (a0[2] + a0[3])) + ((a1[0] + a1[1]) + (a1[2] + a1[3]));
                    l1 = ((b0[0] + b0[1]) + (b0[2] + b0[3])) + ((b1[0] + b1[1]) + (b1[2] + b1[3]));
                    if (lane < 8) {
                        const uint32_t tgt = 4 * b + (lane >> 1);
                        st_async4(mapa(mb_ + A_ST + j * 32 + (lane & 1) * 16, tgt), __float_as_uint(m0), __float_as_uint(l0),
                                  __float_as_uint(m1), __float_as_uint(l1), mapa(XBAR(1), tgt));
                    }
                }
            }
            PROF(4);
            {
                float o0[4] = {}, o1[4] = {};
                const int ch = 2 * w + (mi & 1);
                const uint32_t voff = sb + (ch >> 3) * 8192 + rr * 128 + (((ch & 7) ^ (rr & 7)) << 4);
                const uint32_t poff = mb_ + A_P + (lane & 7) * 1040 + (lane >> 3) * 16;
#pragma unroll 1
                for (int c = 0; c < 8; c++) {
                    uint32_t pf[2][4];
                    ldsm4(pf[0], poff + c * 128);
                    ldsm4(pf[1], poff + c * 128 + 64);
                    mbar_wait(FULL(s), ph);
#pragma unroll
                    for (int ks = 0; ks < 4; ks++) {
                        uint32_t a[4];
                        ldsm4t(a, voff + s * SLOT + ks * 2048);
                        if (ks & 1) mma(o1, a[0], a[1], a[2], a[3], pf[ks >> 1][2], pf[ks >> 1][3]);
                        else mma(o0, a[0], a[1], a[2], a[3], pf[ks >> 1][0], pf[ks >> 1][1]);
                    }
                    __syncwarp();
                    if (lane == 0) mbar_arrive(EMPTY(s));
                    if (++s == NSLOT) { s = 0; ph ^= 1; }
                }
                PROF(5);
                if (hq < 2) {
                    const uint32_t d = mb_ + A_OP + h0 * 544 + (16 * w + grp) * 4;
                    sts1(d, o0[0] + o1[0]);
                    sts1(d + 544, o0[1] + o1[1]);
                    sts1(d + 32, o0[2] + o1[2]);
                    sts1(d + 544 + 32, o0[3] + o1[3]);
                }
            }
            if (w < 4) {
                mbar_wait(XBAR(1), 0);
                float f[4];
                {
                    float mm[4], ll[4];
#pragma unroll
                    for (int i = 0; i < 4; i++) { mm[i] = lds1(mb_ + A_ST + i * 32 + j * 8); ll[i] = lds1(mb_ + A_ST + i * 32 + j * 8 + 4); }
                    const float M = fmaxf(fmaxf(mm[0], mm[1]), fmaxf(mm[2], mm[3]));
#pragma unroll
                    for (int i = 0; i < 4; i++) f[i] = ex2((mm[i] - M) * L2E);
                    const float inv = rcp_((ll[0] * f[0] + ll[1] * f[1]) + (ll[2] * f[2] + ll[3] * f[3]));
#pragma unroll
                    for (int i = 0; i < 4; i++) f[i] *= inv;
                }
                bar_sync(1, 256);
                const uint4 v = lds4u(mb_ + A_OP + w * 544 + lane * 16);
                const uint32_t tgt = 4 * b + w;
                st_async4(mapa(mb_ + A_RS + j * 512 + lane * 16, tgt), v.x, v.y, v.z, v.w, mapa(XBAR(2), tgt));
                const int tg2 = t >> 4, pc = t & 15;
                const uint32_t da = mapa(mb_ + A_O + b * 1040 + j * 256 + pc * 16, tg2), db = mapa(XBAR(3), tg2);
                mbar_wait(XBAR(2), 0);
                float u[4][8];
#pragma unroll
                for (int i = 0; i < 4; i++) {
                    lds4(*reinterpret_cast<float(*)[4]>(&u[i][0]), mb_ + A_RS + i * 512 + pc * 32);
                    lds4(*reinterpret_cast<float(*)[4]>(&u[i][4]), mb_ + A_RS + i * 512 + pc * 32 + 16);
                }
                float o8[8];
#pragma unroll
                for (int k = 0; k < 8; k++) o8[k] = (u[0][k] * f[0] + u[1][k] * f[1]) + (u[2][k] * f[2] + u[3][k] * f[3]);
                st_async4(da, pack2(o8[0], o8[1]), pack2(o8[2], o8[3]), pack2(o8[4], o8[5]), pack2(o8[6], o8[7]), db);
            } else {
                bar_arrive(1, 256);
            }
            const uint32_t tag = (ep + 1) & 1;
            {
                float* pub = p.attn_part + g * 1024 + r * 128 + lane * 4;
                uint32_t oa = mb_ + A_O + act_off, gp_ld = mb_ + A_GP + lane * 16;
                asm volatile("" : "+l"(pub), "+r"(oa), "+r"(gp_ld), "+r"(gp_st));
                uint32_t wf[3][4][4];
#pragma unroll
                for (int c = 0; c < 3; c++) {
                    mbar_wait(FULL(s), ph);
#pragma unroll
                    for (int k = 0; k < 4; k++) ldsm4t(wf[c][k], wt_off + s * SLOT + k * 2048);
                    if (++s == NSLOT) { s = 0; ph ^= 1; }
                }
                uint32_t wl = wt_off + s * SLOT, fl = FULL(s);
                asm volatile("" : "+r"(wl), "+r"(fl));
                mbar_wait(XBAR(3), 0);
                PROF(6);
                uint32_t bf[4][2][4];
#pragma unroll
                for (int c = 0; c < 4; c++) { ldsm4(bf[c][0], oa + c * 256); ldsm4(bf[c][1], oa + c * 256 + 64); }
                float acc[4][4] = {};
#pragma unroll
                for (int c = 0; c < 3; c++)
#pragma unroll
                    for (int k = 0; k < 4; k++)
                        mma(acc[k], wf[c][k][0], wf[c][k][1], wf[c][k][2], wf[c][k][3], bf[c][k >> 1][(k & 1) * 2], bf[c][k >> 1][(k & 1) * 2 + 1]);
                mbar_wait(fl, ph);
                PROF(9);
#pragma unroll
                for (int k = 0; k < 4; k++) {
                    uint32_t a[4];
                    ldsm4t(a, wl + k * 2048);
                    mma(acc[k], a[0], a[1], a[2], a[3], bf[3][k >> 1][(k & 1) * 2], bf[3][k >> 1][(k & 1) * 2 + 1]);
                }
                if (hq == 0) {
                    sts1(gp_st, (acc[0][0] + acc[1][0]) + (acc[2][0] + acc[3][0]));
                    sts1(gp_st + 256, (acc[0][1] + acc[1][1]) + (acc[2][1] + acc[3][1]));
                    sts1(gp_st + 32, (acc[0][2] + acc[1][2]) + (acc[2][2] + acc[3][2]));
                    sts1(gp_st + 256 + 32, (acc[0][3] + acc[1][3]) + (acc[2][3] + acc[3][3]));
                }
                if (w == 2) {
                    bar_sync(1, 256);
                    float u[4], v[4];
                    lds4(u, gp_ld); lds4(v, gp_ld + 512);
                    exch_tag4(pub, u[0] + v[0], u[1] + v[1], u[2] + v[2], u[3] + v[3], tag);
                    PROFL(12);
                } else {
                    bar_arrive(1, 256);
                }
                PROF(7);
            }
            const uint32_t tmask = 0u - tag;
            {
                const int c0 = 16 * (cta >> 1) + 4 * (cta & 1);
                const float* src = w == 0 ? p.attn_part + grp * 1024 + (c0 >> 6) * 128 + (hq >> 1) * 64 + (c0 & 63) + (hq & 1) * 8
                                          : p.out_part + cl * 4096 + (8 * (w - 1) + grp) * 64 + r * 8 + 2 * hq;
                __nv_bfloat16* outp = p.out + c0 + hq;
                unsigned* epp = p.epoch;
                uint32_t fs = mb_ + A_RS + w * 64 + hq * 16;
                asm volatile("" : "+l"(outp), "+l"(epp), "+l"(src), "+r"(fs));
                float d4[4];
                if (w == 0) {
                    const uint4 v = poll_packet(src, tmask);
                    d4[0] = __uint_as_float(v.x); d4[1] = __uint_as_float(v.y); d4[2] = __uint_as_float(v.z); d4[3] = __uint_as_float(v.w);
                } else {
                    uint2 v;
                    int it = 0;
                    do { v = ld_poll2(src); } while (__any_sync(0xffffffffu, ((v.x ^ tmask) | (v.y ^ tmask)) & 1u) && ++it < POLL_LIMIT);
                    d4[0] = bfhi(v.x); d4[1] = bflo(v.x); d4[2] = bfhi(v.y); d4[3] = bflo(v.y);
                }
#pragma unroll
                for (int o = 4; o <= 16; o <<= 1) {
#pragma unroll
                    for (int i = 0; i < 4; i++) d4[i] += __shfl_xor_sync(0xffffffffu, d4[i], o);
                }
                if (w) {
                    if (lane < 4) sts4u(fs, __float_as_uint(d4[0]), __float_as_uint(d4[1]), __float_as_uint(d4[2]), __float_as_uint(d4[3]));
                    bar_arrive(3, 256);
                } else {
                    if (lane < 4) {
                        const uint32_t d = mb_ + A_RS + (hq & 1) * 8 + (hq >> 1) * 4;
                        sts1(d, bfr(bflo(xr.x) + bfr(d4[0])));
                        sts1(d + 16, bfr(bfhi(xr.x) + bfr(d4[1])));
                        sts1(d + 32, bfr(bflo(xr.y) + bfr(d4[2])));
                        sts1(d + 48, bfr(bfhi(xr.y) + bfr(d4[3])));
                    }
                    PROF(10);
                    bar_sync(3, 256);
                    float u[8][4];
#pragma unroll
                    for (int i = 0; i < 8; i++) lds4(u[i], fs + i * 64);
#pragma unroll
                    for (int k = 0; k < 4; k++) d4[k] = u[0][k] + bfr(((u[1][k] + u[2][k]) + (u[3][k] + u[4][k])) + ((u[5][k] + u[6][k]) + u[7][k]));
                    if (lane < 4) {
                        outp[0] = __float2bfloat16_rn(d4[0]);
                        outp[512] = __float2bfloat16_rn(d4[1]);
                        outp[8] = __float2bfloat16_rn(d4[2]);
                        outp[520] = __float2bfloat16_rn(d4[3]);
                        if (cta == 0 && lane == 0) *epp = ep + 1;
                    }
                    PROF(11);
                }
            }
            PROF_DUMP();
        }
    } else {
        const int m = cta - kAttn;
        unsigned ep;
        asm volatile("ld.relaxed.gpu.global.u32 %0, [%1];" : "=r"(ep) : "l"(p.epoch) : "memory");
        if (w == 9) {
            bar_sync(0, kThreads);
            if (lane == 0) {
#pragma unroll 1
                for (int i = 0; i < 10; i++) {
                    spin_until(ns0 + p.mlp_t0 + (i < 8 ? i : 2 * i - 8) * p.mlp_dt);
                    if (i < 8) tma2d(sb + (i & 1) * 32768 + (i >> 1) * 8192, (i & 1) ? &tm_u : &tm_g, 32 * m, 128 * (i >> 1), MFULL(i));
                    else tma3d(sb + M_DOWN + (i - 8) * 16384, &tm_d, 0, 32 * m, 4 * (i - 8), MFULL(i));
                }
            }
        } else if (w == 8) {
            bar_arrive(0, kThreads);
            uint2 xv;
            asm volatile("ld.global.nc.v2.u32 {%0,%1}, [%2];" : "=r"(xv.x), "=r"(xv.y) : "l"(p.x + (lane >> 4) * 512 + 64 * r + (lane & 15) * 4));
            cluster_wait();
            const uint32_t dst = mb_ + M_H + (lane >> 4) * 1040 + 128 * r + ((lane & 15) >> 1) * 16;
            uint32_t da[4], db[4], gl = mb_ + M_G3 + lane * 16;
#pragma unroll
            for (int i = 0; i < 4; i++) { da[i] = mapa(dst, 2 * i + (lane & 1)); db[i] = mapa(XBAR(3), 2 * i + (lane & 1)); }
            uint32_t sl = mb_ + M_SP + (lane >> 4) * 64;
            uint32_t sa = mapa(sl + r * 8, lane & 7), sbar = mapa(XBAR(2), lane & 7);
            float xf[4] = {bflo(xv.x), bfhi(xv.x), bflo(xv.y), bfhi(xv.y)};
            asm volatile("" : "+r"(gl), "+r"(sl), "+r"(sa), "+r"(sbar), "+f"(xf[0]), "+f"(xf[1]), "+f"(xf[2]), "+f"(xf[3]));
            bar_sync(3, 288);
            float u[8][4], a4[4];
#pragma unroll
            for (int i = 0; i < 8; i++) lds4(u[i], gl + i * 512);
#pragma unroll
            for (int k = 0; k < 4; k++) a4[k] = xf[k] + bfr(((u[0][k] + u[1][k]) + (u[2][k] + u[3][k])) + ((u[4][k] + u[5][k]) + (u[6][k] + u[7][k])));
            const uint32_t hw0 = pack2(a4[0], a4[1]), hw1 = pack2(a4[2], a4[3]);
            const uint32_t ow0 = __shfl_xor_sync(0xffffffffu, hw0, 1), ow1 = __shfl_xor_sync(0xffffffffu, hw1, 1);
            const bool odd = lane & 1;
            const uint32_t e0 = odd ? ow0 : hw0, e1 = odd ? ow1 : hw1, e2 = odd ? hw0 : ow0, e3 = odd ? hw1 : ow1;
#pragma unroll
            for (int i = 0; i < 4; i++) st_async4(da[i], e0, e1, e2, e3, db[i]);
            PROF(9);
            {
                const float h0 = bflo(hw0), h1 = bfhi(hw0), h2 = bflo(hw1), h3 = bfhi(hw1);
                float s1 = (h0 + h1) + (h2 + h3), s2 = fmaf(h0, h0, h1 * h1) + fmaf(h2, h2, h3 * h3);
#pragma unroll
                for (int o = 8; o; o >>= 1) { s1 += __shfl_xor_sync(0xffffffffu, s1, o); s2 += __shfl_xor_sync(0xffffffffu, s2, o); }
                if (!(lane & 8))
                    asm volatile("st.async.weak.shared::cluster.mbarrier::complete_tx::bytes.v2.b32 [%0], {%1,%2}, [%3];"
                                 ::"r"(sa), "r"(__float_as_uint(s1)), "r"(__float_as_uint(s2)), "r"(sbar) : "memory");
                mbar_wait(XBAR(2), 0);
                float u0[4], u1[4], u2[4], u3[4];
                lds4(u0, sl); lds4(u1, sl + 16); lds4(u2, sl + 32); lds4(u3, sl + 48);
                const float mean = (((u0[0] + u0[2]) + (u1[0] + u1[2])) + ((u2[0] + u2[2]) + (u3[0] + u3[2]))) * (1.f / 512.f);
                const float msq = (((u0[1] + u0[3]) + (u1[1] + u1[3])) + ((u2[1] + u2[3]) + (u3[1] + u3[3]))) * (1.f / 512.f);
                const float var = fmaxf(fmaf(-mean, mean, msq), 0.f);
                if ((lane & 15) == 0) sts2(mb_ + M_ST + (lane >> 4) * 8, bfr(mean), ln_rden(var));
            }
            bar_arrive(2, 288);
            PROF(10);
            PROF_DUMP();
        } else {
            if (t < 32) asm volatile("st.shared.u32 [%0], %1;" ::"r"(mb_ + M_CS + (t & 31) * 4), "r"(0x3f803f80u) : "memory");
            bar_sync(0, kThreads);
            cluster_wait();
            const int mi = lane >> 3, rr = (lane & 7) + (mi >> 1) * 8;
            float* dout = p.out_part + w * 4096 + m * 64 + hq * 16 + 2 * grp;
            const int bb = (w >> 1) & 1, mat = lane >> 4, col = (w & 1) * 16 + (lane & 15);
            uint32_t tag = (ep + 1) & 1, trnd = (ep & 1) << 16;
            uint32_t ha = grp < 6 ? mb_ + M_H + (grp & 1) * 1040 + w * 128 + hq * 4 : mb_ + M_CS + hq * 4;
            uint32_t pst = hq == 3 ? mb_ + M_CSP + w * 256 + grp * 4 : mb_ + M_PART + w * 768 + ((hq >> 1) * 48 + (hq & 1) * 16 + grp) * 4;
            uint32_t pst2 = hq == 3 ? pst + 128 : pst + 256, po1 = hq == 3 ? 32 : 384, po2 = hq == 3 ? 64 : 32;
            uint32_t pld = mb_ + M_PART + bb * 384 + (mat * 48 + col) * 4, cld = mb_ + M_CSP + (mat * 32 + col) * 4;
            uint32_t sld = mb_ + M_ST + bb * 8, hst = mb_ + M_HH + bb * 80 + col * 2, hld = mb_ + M_HH + (grp & 1) * 80 + hq * 4;
            uint32_t dn = sb + M_DOWN + w * 4096 + rr * 128 + (((mi & 1) ^ (rr & 7)) << 4), xb = XBAR(3);
            asm volatile("" : "+l"(dout), "+r"(tag), "+r"(trnd), "+r"(ha), "+r"(pst), "+r"(pst2), "+r"(po1), "+r"(po2), "+r"(pld), "+r"(cld), "+r"(sld), "+r"(hst), "+r"(hld), "+r"(dn), "+r"(xb));
            uint32_t wf[4][4][4];
            const uint32_t fa = MFULL(w & 6), fb = fa + 8;
            bool ready;
            {
                int it = 0;
                do { ready = mbar_test(fa, 0) && mbar_test(fb, 0); } while (!ready && nsclock() - ns0 < (uint32_t)p.poll_t0 && ++it < SPIN_LIMIT);
            }
            ready = __all_sync(0xffffffffu, ready);
            auto stage_gu = [&]() {
                mbar_wait(fa, 0);
                mbar_wait(fb, 0);
#pragma unroll
                for (int tl = 0; tl < 4; tl++)
#pragma unroll
                    for (int ks = 0; ks < 4; ks++) {
                        const int row = 64 * w + 16 * ks + rr;
                        const int ch = 2 * (tl & 1) + (mi & 1);
                        ldsm4t(wf[tl][ks], sb + (tl >> 1) * 32768 + row * 64 + ((ch ^ ((row >> 1) & 3)) << 4));
                    }
                PROF(0);
            };
            if (ready) stage_gu();
            {
                spin_until(ns0 + p.poll_t0);
                const uint4 v = poll_packet(p.attn_part + w * 1024 + r * 128 + lane * 4, 0u - tag);
                sts4u(mb_ + M_G3 + w * 512 + lane * 16, v.x, v.y, v.z, v.w);
                bar_arrive(3, 288);
            }
            if (!ready) stage_gu();
            PROF(4);
            uint32_t df[4][2][4];
            const uint32_t fd = MFULL(8 + (w >> 2));
            bool early = false;
            if (NSLOT > 6) {
                int it = 0;
                do { early = mbar_test(fd, 0); } while (!early && !mbar_test(xb, 0) && ++it < MBAR_LIMIT);
                early = __all_sync(0xffffffffu, early);
            }
            auto stage_dn = [&]() {
                mbar_wait(fd, 0);
#pragma unroll
                for (int tl = 0; tl < 4; tl++)
#pragma unroll
                    for (int ks = 0; ks < 2; ks++) ldsm4t(df[tl][ks], (dn ^ (tl << 5)) + ks * 2048);
            };
            if (early) stage_dn();
            {
                {
                    mbar_wait(xb, 0);
                    PROF(1);
                    uint32_t hf[8];
#pragma unroll
                    for (int k = 0; k < 8; k++) hf[k] = lds1u(ha + k * 16);
                    float c[4][4] = {};
#pragma unroll
                    for (int ks = 0; ks < 4; ks++)
#pragma unroll
                        for (int tl = 0; tl < 4; tl++)
                            mma(c[tl], wf[tl][ks][0], wf[tl][ks][1], wf[tl][ks][2], wf[tl][ks][3], hf[2 * ks], hf[2 * ks + 1]);
                    const bool h3 = hq == 3;
                    const float v0 = hq == 0 ? c[0][0] : hq == 1 ? c[1][0] : hq == 2 ? c[2][0] : c[0][0];
                    const float v1 = hq == 0 ? c[0][1] : hq == 1 ? c[1][1] : hq == 2 ? c[2][1] : c[0][2];
                    const float v2 = hq == 0 ? c[0][2] : hq == 1 ? c[1][2] : hq == 2 ? c[2][2] : c[1][0];
                    const float v3 = hq == 0 ? c[0][3] : hq == 1 ? c[1][3] : hq == 2 ? c[2][3] : c[1][2];
                    sts1(pst, v0); sts1(pst + po1, v1); sts1(pst + po2, v2); sts1(pst + po1 + po2, v3);
                    if (hq == 0 || h3) {
                        sts1(pst2, h3 ? c[2][0] : c[3][0]); sts1(pst2 + po1, h3 ? c[2][2] : c[3][1]);
                        sts1(pst2 + po2, h3 ? c[3][0] : c[3][2]); sts1(pst2 + po1 + po2, h3 ? c[3][2] : c[3][3]);
                    }
                    if (w < 4) {
                        bar_sync(2, 288);
                        float f[8], cf[8];
#pragma unroll
                        for (int i = 0; i < 8; i++) f[i] = lds1(pld + i * 768);
#pragma unroll
                        for (int i = 0; i < 8; i++) cf[i] = lds1(cld + i * 256);
                        const float mean = lds1(sld), rs = lds1(sld + 4);
                        const float g = bfr(fmaf(-mean, tree_sum(cf), tree_sum(f)) * rs);
                        const float u = __shfl_xor_sync(0xffffffffu, g, 16);
                        const float e = ex2(g * fmaf(g * g, -0.10294324f, -2.3022082f));
                        const float ge = bfr(g * rcp_(1.f + e));
                        if (lane < 16) sts16(hst, ge * u);
                        PROF(2);
                    } else {
                        bar_arrive(2, 288);
                    }
                }
            }
            if (!early) stage_dn();
            PROF(5);
            bar_sync(1, 256);
            uint32_t hf[4];
#pragma unroll
            for (int k = 0; k < 4; k++) hf[k] = lds1u(hld + k * 16);
            float c[4][4] = {};
#pragma unroll
            for (int ks = 0; ks < 2; ks++)
#pragma unroll
                for (int tl = 0; tl < 4; tl++) mma(c[tl], df[tl][ks][0], df[tl][ks][1], df[tl][ks][2], df[tl][ks][3], hf[2 * ks], hf[2 * ks + 1]);
            {
                float v[4];
#pragma unroll
                for (int k = 0; k < 4; k++) {
                    const float lo = (hq & 1) ? c[1][k] : c[0][k], hi = (hq & 1) ? c[3][k] : c[2][k];
                    v[k] = (hq & 2) ? hi : lo;
                }
                st_mail2(dout, pack_tag(v[0], v[1], tag, trnd), pack_tag(v[2], v[3], tag, trnd));
            }
            PROF(3);
            PROF_DUMP();
        }
    }
}

typedef CUresult (*EncodeFn)(CUtensorMap*, CUtensorMapDataType, cuuint32_t, void*, const cuuint64_t*, const cuuint64_t*,
                             const cuuint32_t*, const cuuint32_t*, CUtensorMapInterleave, CUtensorMapSwizzle,
                             CUtensorMapL2promotion, CUtensorMapFloatOOBfill);

void make_map(EncodeFn enc, CUtensorMap* m, const void* ptr, int rank, const cuuint64_t* dims, const cuuint64_t* strides,
              const cuuint32_t* box, CUtensorMapSwizzle sw) {
    const cuuint32_t es[3] = {1, 1, 1};
    enc(m, CU_TENSOR_MAP_DATA_TYPE_BFLOAT16, rank, const_cast<void*>(ptr), dims, strides, box, es, CU_TENSOR_MAP_INTERLEAVE_NONE, sw,
        CU_TENSOR_MAP_L2_PROMOTION_L2_128B, CU_TENSOR_MAP_FLOAT_OOB_FILL_NONE);
}

}

static int g_pace = 310, g_lead = 0, g_mlp_t0 = 7700, g_mlp_dt = 175, g_poll_t0 = 8700, g_small = -1;

extern "C" void kernel_launch(void* const* d_in, const int* in_sizes, int n_in, void* d_out, int out_size) {
    (void)in_sizes; (void)n_in; (void)out_size;
    static EncodeFn enc = nullptr;
    static void *a_epoch, *a_mail;
    if (!enc) {
        void* fn = nullptr;
        cudaDriverEntryPointQueryResult qr;
        cudaGetDriverEntryPoint("cuTensorMapEncodeTiled", &fn, cudaEnableDefault, &qr);
        enc = (EncodeFn)fn;
        cudaFuncSetAttribute(fused_decode<kBig>, cudaFuncAttributeMaxDynamicSharedMemorySize, smem_bytes(kBig));
        cudaFuncSetAttribute(fused_decode<kSmall>, cudaFuncAttributeMaxDynamicSharedMemorySize, smem_bytes(kSmall));
        cudaGetSymbolAddress(&a_epoch, g_epoch);
        cudaGetSymbolAddress(&a_mail, g_mail);
    }
    CUtensorMap tq, tk, tv, to, tg, tu, td;
    {
        const cuuint64_t d[3] = {4096, 512, 1}, s[2] = {8192, 4194304}; const cuuint32_t bx[3] = {64, 128, 1};
        make_map(enc, &tq, d_in[3], 3, d, s, bx, CU_TENSOR_MAP_SWIZZLE_128B);
    }
    {
        const cuuint64_t d[3] = {64, 131072, 2}, s[2] = {256, 128}; const cuuint32_t bx[3] = {64, 64, 2};
        make_map(enc, &tk, d_in[1], 3, d, s, bx, CU_TENSOR_MAP_SWIZZLE_128B);
        make_map(enc, &tv, d_in[2], 3, d, s, bx, CU_TENSOR_MAP_SWIZZLE_128B);
    }
    {
        const cuuint64_t d[3] = {512, 4096, 1}, s[2] = {1024, 4194304}; const cuuint32_t bx[3] = {64, 128, 1};
        make_map(enc, &to, d_in[4], 3, d, s, bx, CU_TENSOR_MAP_SWIZZLE_128B);
    }
    {
        const cuuint64_t d[2] = {1792, 512}, s[1] = {3584}; const cuuint32_t bx[2] = {32, 128};
        make_map(enc, &tg, d_in[6], 2, d, s, bx, CU_TENSOR_MAP_SWIZZLE_64B);
        make_map(enc, &tu, d_in[7], 2, d, s, bx, CU_TENSOR_MAP_SWIZZLE_64B);
    }
    {
        const cuuint64_t d[3] = {64, 1792, 8}, s[2] = {1024, 128}; const cuuint32_t bx[3] = {64, 32, 4};
        make_map(enc, &td, d_in[8], 3, d, s, bx, CU_TENSOR_MAP_SWIZZLE_128B);
    }
    Params p;
    p.x = (const __nv_bfloat16*)d_in[0];
    p.out = (__nv_bfloat16*)d_out;
    p.epoch = (unsigned*)a_epoch;
    p.attn_part = (float*)a_mail;
    p.out_part = p.attn_part + 8 * 1024;
    p.pace = g_pace; p.lead = g_lead; p.mlp_t0 = g_mlp_t0; p.mlp_dt = g_mlp_dt; p.poll_t0 = g_poll_t0;
    cudaLaunchConfig_t cfg = {};
    cfg.gridDim = dim3(kCtas);
    cfg.blockDim = dim3(kThreads);
    cfg.stream = cudaStreamPerThread;
    cudaLaunchAttribute at[1];
    at[0].id = cudaLaunchAttributeClusterDimension;
    at[0].val.clusterDim.x = 8; at[0].val.clusterDim.y = 1; at[0].val.clusterDim.z = 1;
    cfg.attrs = at;
    cfg.numAttrs = 1;
    if (g_small < 0) {
        int n = 0;
        cfg.dynamicSmemBytes = smem_bytes(kBig);
        cudaError_t e = cudaOccupancyMaxActiveClusters(&n, fused_decode<kBig>, &cfg);
        g_small = (e != cudaSuccess || n < kCtas / 8) ? 1 : 0;
        (void)cudaGetLastError();
    }
    if (g_small) {
        cfg.dynamicSmemBytes = smem_bytes(kSmall);
        cudaLaunchKernelEx(&cfg, fused_decode<kSmall>, tq, tk, tv, to, tg, tu, td, p);
    } else {
        cfg.dynamicSmemBytes = smem_bytes(kBig);
        cudaLaunchKernelEx(&cfg, fused_decode<kBig>, tq, tk, tv, to, tg, tu, td, p);
    }
}
```

```cpp
#include <cuda_runtime.h>
#include <cuda_bf16.h>
#include <cuda.h>
#include <stdint.h>

namespace {

constexpr int kAttn = 64, kMlp = 56, kCtas = kAttn + kMlp;
constexpr int SLOT = 16384;
constexpr int kBig = 13, kSmall = 6;
constexpr int A_XN = 0;
constexpr int A_O = A_XN + 2080;
constexpr int A_Q = A_O + 2080;
constexpr int A_P = A_Q + 1088;
constexpr int A_RS = A_P + 4160;
constexpr int A_OP = A_RS + 2048;
constexpr int A_ST = A_OP + 2176;
constexpr int A_WM = A_ST + 128;
constexpr int A_WS = A_WM + 128;
constexpr int A_GP = A_WS + 128;
constexpr int A_END = A_GP + 1024;
constexpr int M_DOWN = 65536;
constexpr int M_H = 0;
constexpr int M_PART = M_H + 2080;
constexpr int M_CSP = M_PART + 6144;
constexpr int M_CS = M_CSP + 2048;
constexpr int M_HH = M_CS + 256;
constexpr int M_ST = M_HH + 160;
constexpr int M_G3 = M_ST + 16;
constexpr int M_SP = M_G3 + 4096;
constexpr int M_END = M_SP + 128;
constexpr int OFF_BAR = ((A_END > M_END ? A_END : M_END) + 15) / 16 * 16;
constexpr int OFF_PROF = OFF_BAR + 36 * 8;
constexpr int MISC_BYTES = OFF_PROF + 64;
constexpr int kThreads = 320;
constexpr int smem_bytes(int nslot) { return nslot * SLOT + MISC_BYTES + 1024; }

constexpr int POLL_LIMIT = 200000;
constexpr int MBAR_LIMIT = 20000000;
constexpr int SPIN_LIMIT = 2000000;

struct Params {
    const __nv_bfloat16* x;
    __nv_bfloat16* out;
    unsigned* epoch;
    float* attn_part;
    float* out_part;
    int pace, lead, stag, mlp_t0, mlp_dt, mlp_stag, poll_t0;
};

__device__ unsigned g_epoch;
__device__ __align__(1024) float g_mail[(8 + 32) * 1024];
#define PROF(i) do {} while (0)
#define PROF_DUMP() do {} while (0)
#define PROFL(i) do {} while (0)
__device__ __forceinline__ uint32_t clock32() { uint32_t c; asm volatile("mov.u32 %0, %%clock;" : "=r"(c) :: "memory"); return c; }

__device__ __forceinline__ uint32_t nsclock() { uint32_t c; asm volatile("mov.u32 %0, %%globaltimer_lo;" : "=r"(c) :: "memory"); return c; }
__device__ __forceinline__ uint32_t s2u(const void* p) { return (uint32_t)__cvta_generic_to_shared(p); }
__device__ __forceinline__ void mbar_init(uint32_t a, int c) { asm volatile("mbarrier.init.shared::cta.b64 [%0], %1;" ::"r"(a), "r"(c) : "memory"); }
__device__ __forceinline__ void mbar_expect(uint32_t a, uint32_t b) { asm volatile("mbarrier.arrive.expect_tx.shared::cta.b64 _, [%0], %1;" ::"r"(a), "r"(b) : "memory"); }
__device__ __forceinline__ void mbar_arrive(uint32_t a) { asm volatile("mbarrier.arrive.shared::cta.b64 _, [%0];" ::"r"(a) : "memory"); }
__device__ __forceinline__ void mbar_wait(uint32_t a, uint32_t ph) {
    uint32_t ok; int it = 0;
    do {
        asm volatile("{ .reg .pred p; mbarrier.try_wait.parity.shared::cta.b64 p, [%1], %2; selp.u32 %0, 1, 0, p; }" : "=r"(ok) : "r"(a), "r"(ph) : "memory");
    } while (!ok && ++it < MBAR_LIMIT);
}
__device__ __forceinline__ bool mbar_test(uint32_t a, uint32_t ph) {
    uint32_t ok;
    asm volatile("{ .reg .pred p; mbarrier.test_wait.parity.shared::cta.b64 p, [%1], %2; selp.u32 %0, 1, 0, p; }" : "=r"(ok) : "r"(a), "r"(ph) : "memory");
    return ok;
}
__device__ __forceinline__ void tma2d(uint32_t dst, const CUtensorMap* m, int c0, int c1, uint32_t bar) {
    asm volatile("cp.async.bulk.tensor.2d.shared::cluster.global.mbarrier::complete_tx::bytes [%0], [%1, {%3, %4}], [%2];"
                 ::"r"(dst), "l"(m), "r"(bar), "r"(c0), "r"(c1) : "memory");
}
__device__ __forceinline__ void tma3d(uint32_t dst, const CUtensorMap* m, int c0, int c1, int c2, uint32_t bar) {
    asm volatile("cp.async.bulk.tensor.3d.shared::cluster.global.mbarrier::complete_tx::bytes [%0], [%1, {%3, %4, %5}], [%2];"
                 ::"r"(dst), "l"(m), "r"(bar), "r"(c0), "r"(c1), "r"(c2) : "memory");
}
__device__ __forceinline__ uint32_t mapa(uint32_t a, uint32_t rank) { uint32_t r; asm("mapa.shared::cluster.u32 %0, %1, %2;" : "=r"(r) : "r"(a), "r"(rank)); return r; }
__device__ __forceinline__ void st_async4(uint32_t dst, uint32_t a, uint32_t b, uint32_t c, uint32_t d, uint32_t bar) {
    asm volatile("st.async.weak.shared::cluster.mbarrier::complete_tx::bytes.v4.b32 [%0], {%1,%2,%3,%4}, [%5];"
                 ::"r"(dst), "r"(a), "r"(b), "r"(c), "r"(d), "r"(bar) : "memory");
}
__device__ __forceinline__ void ldsm4(uint32_t (&r)[4], uint32_t a) {
    asm volatile("ldmatrix.sync.aligned.m8n8.x4.shared.b16 {%0,%1,%2,%3}, [%4];" : "=r"(r[0]), "=r"(r[1]), "=r"(r[2]), "=r"(r[3]) : "r"(a) : "memory");
}
__device__ __forceinline__ void ldsm4t(uint32_t (&r)[4], uint32_t a) {
    asm volatile("ldmatrix.sync.aligned.m8n8.x4.trans.shared.b16 {%0,%1,%2,%3}, [%4];" : "=r"(r[0]), "=r"(r[1]), "=r"(r[2]), "=r"(r[3]) : "r"(a) : "memory");
}
__device__ __forceinline__ void mma(float (&c)[4], uint32_t a0, uint32_t a1, uint32_t a2, uint32_t a3, uint32_t b0, uint32_t b1) {
    asm volatile("mma.sync.aligned.m16n8k16.row.col.f32.bf16.bf16.f32 {%0,%1,%2,%3}, {%4,%5,%6,%7}, {%8,%9}, {%0,%1,%2,%3};"
                 : "+f"(c[0]), "+f"(c[1]), "+f"(c[2]), "+f"(c[3]) : "r"(a0), "r"(a1), "r"(a2), "r"(a3), "r"(b0), "r"(b1));
}
__device__ __forceinline__ void bar_sync(int id, int n) { asm volatile("bar.sync %0, %1;" ::"r"(id), "r"(n) : "memory"); }
__device__ __forceinline__ void bar_arrive(int id, int n) { asm volatile("bar.arrive %0, %1;" ::"r"(id), "r"(n) : "memory"); }
__device__ __forceinline__ void cluster_arrive() { asm volatile("barrier.cluster.arrive.relaxed.aligned;" ::: "memory"); }
__device__ __forceinline__ void cluster_wait() { asm volatile("barrier.cluster.wait.acquire.aligned;" ::: "memory"); }
__device__ __forceinline__ uint32_t pack2(float lo, float hi) { uint32_t r; asm("cvt.rn.bf16x2.f32 %0, %1, %2;" : "=r"(r) : "f"(hi), "f"(lo)); return r; }
__device__ __forceinline__ float bfr(float v) { return __uint_as_float(pack2(0.f, v)); }
__device__ __forceinline__ float bflo(uint32_t v) { return __uint_as_float(v << 16); }
__device__ __forceinline__ float bfhi(uint32_t v) { return __uint_as_float(v & 0xffff0000u); }
__device__ __forceinline__ float ex2(float v) { float r; asm("ex2.approx.ftz.f32 %0, %1;" : "=f"(r) : "f"(v)); return r; }
__device__ __forceinline__ uint4 ld_poll(const float* p) {
    uint4 v;
    asm volatile("ld.relaxed.gpu.global.v4.u32 {%0,%1,%2,%3}, [%4];" : "=r"(v.x), "=r"(v.y), "=r"(v.z), "=r"(v.w) : "l"(p) : "memory");
    return v;
}
__device__ __forceinline__ void st_mail4(float* p, uint32_t v) {
    asm volatile("st.relaxed.gpu.global.v4.u32 [%0], {%1,%1,%1,%1};" ::"l"(p), "r"(v) : "memory");
}
__device__ __forceinline__ void exch_tag4(float* p, float a, float b, float c, float d, uint32_t tag) {
    const uint32_t x = (__float_as_uint(a) & ~1u) | tag, y = (__float_as_uint(b) & ~1u) | tag;
    const uint32_t z = (__float_as_uint(c) & ~1u) | tag, u = (__float_as_uint(d) & ~1u) | tag;
    asm volatile("{ .reg .b128 t, o; mov.b128 t, {%1, %2}; atom.relaxed.gpu.global.exch.b128 o, [%0], t; }" ::"l"(p),
                 "l"((unsigned long long)x | ((unsigned long long)y << 32)), "l"((unsigned long long)z | ((unsigned long long)u << 32)) : "memory");
}
__device__ __forceinline__ uint32_t pack_tag(float hi, float lo, uint32_t tag, uint32_t trnd) {
    return pack2(0.f, hi) | (((__float_as_uint(lo) + trnd) >> 17) << 1) | tag;
}
__device__ __forceinline__ void st_mail2(float* p, uint32_t x, uint32_t y) {
    asm volatile("st.relaxed.gpu.global.v2.u32 [%0], {%1,%2};" ::"l"(p), "r"(x), "r"(y) : "memory");
}
__device__ __forceinline__ uint2 ld_poll2(const float* p) {
    uint2 v;
    asm volatile("ld.relaxed.gpu.global.v2.u32 {%0,%1}, [%2];" : "=r"(v.x), "=r"(v.y) : "l"(p) : "memory");
    return v;
}
__device__ __forceinline__ void lds4(float (&v)[4], uint32_t a) {
    asm volatile("ld.shared.v4.f32 {%0,%1,%2,%3}, [%4];" : "=f"(v[0]), "=f"(v[1]), "=f"(v[2]), "=f"(v[3]) : "r"(a) : "memory");
}
__device__ __forceinline__ uint4 lds4u(uint32_t a) {
    uint4 v; asm volatile("ld.shared.v4.u32 {%0,%1,%2,%3}, [%4];" : "=r"(v.x), "=r"(v.y), "=r"(v.z), "=r"(v.w) : "r"(a) : "memory"); return v;
}
__device__ __forceinline__ float lds1(uint32_t a) { float v; asm volatile("ld.shared.f32 %0, [%1];" : "=f"(v) : "r"(a) : "memory"); return v; }
__device__ __forceinline__ uint32_t lds1u(uint32_t a) { uint32_t v; asm volatile("ld.shared.u32 %0, [%1];" : "=r"(v) : "r"(a) : "memory"); return v; }
__device__ __forceinline__ void sts1(uint32_t a, float v) { asm volatile("st.shared.f32 [%0], %1;" ::"r"(a), "f"(v) : "memory"); }
__device__ __forceinline__ void sts2(uint32_t a, float v, float w) { asm volatile("st.shared.v2.f32 [%0], {%1,%2};" ::"r"(a), "f"(v), "f"(w) : "memory"); }
__device__ __forceinline__ void sts16(uint32_t a, float v) {
    asm volatile("{ .reg .b16 lo, hi; mov.b32 {lo, hi}, %1; st.shared.u16 [%0], lo; }" ::"r"(a), "r"(pack2(v, 0.f)) : "memory");
}
__device__ __forceinline__ void sts4u(uint32_t a, uint32_t x, uint32_t y, uint32_t z, uint32_t w) {
    asm volatile("st.shared.v4.u32 [%0], {%1,%2,%3,%4};" ::"r"(a), "r"(x), "r"(y), "r"(z), "r"(w) : "memory");
}

template <int N>
__device__ __forceinline__ float tree_sum(float (&f)[N]) {
#pragma unroll
    for (int d = 1; d < N; d <<= 1)
#pragma unroll
        for (int i = 0; i + d < N; i += 2 * d) f[i] += f[i + d];
    return f[0];
}
__device__ __forceinline__ void spin_until(uint32_t due) {
    int it = 0;
    while ((int)(nsclock() - due) < 0 && ++it < SPIN_LIMIT) {}
}
__device__ __forceinline__ uint4 poll_packet(const float* src, uint32_t tmask) {
    uint4 v;
    int it = 0;
    do {
        v = ld_poll(src);
    } while (__any_sync(0xffffffffu, (((v.x ^ tmask) | (v.y ^ tmask)) | ((v.z ^ tmask) | (v.w ^ tmask))) & 1u) && ++it < POLL_LIMIT);
    return v;
}

__device__ __forceinline__ float rcp_(float v) { float r; asm("rcp.approx.ftz.f32 %0, %1;" : "=f"(r) : "f"(v)); return r; }
__device__ __forceinline__ float sqrt_(float v) { float r; asm("sqrt.approx.ftz.f32 %0, %1;" : "=f"(r) : "f"(v)); return r; }
__device__ __forceinline__ float ln_rden(float var) { return rcp_(bfr(sqrt_(bfr(bfr(var) + 1e-5f)))); }

template <int NSLOT>
__global__ void __launch_bounds__(kThreads, NSLOT <= 6 ? 2 : 1)
fused_decode(const __grid_constant__ CUtensorMap tm_wq, const __grid_constant__ CUtensorMap tm_k,
             const __grid_constant__ CUtensorMap tm_v, const __grid_constant__ CUtensorMap tm_wo,
             const __grid_constant__ CUtensorMap tm_g, const __grid_constant__ CUtensorMap tm_u,
             const __grid_constant__ CUtensorMap tm_d, const Params p) {
    extern __shared__ uint8_t smem_raw[];
    const uint32_t sb = (s2u(smem_raw) + 1023u) & ~1023u;
    const uint32_t mb_ = sb + NSLOT * SLOT;
    const int t = threadIdx.x, w = t >> 5, lane = t & 31, grp = lane >> 2, hq = lane & 3;
    const int cta = blockIdx.x, r = cta & 7, cl = cta >> 3;
    const uint32_t bar0 = mb_ + OFF_BAR;
    const uint32_t ns0 = nsclock();
#define FULL(s) (bar0 + 8 * (s))
#define EMPTY(s) (bar0 + 128 + 8 * (s))
#define XBAR(i) (bar0 + 256 + 8 * (i))
#define MFULL(i) ((i) < 6 ? FULL(i) : EMPTY((i) - 6))
    if (w == 8) {
        if (lane == 0) {
            mbar_init(FULL(0), 1);
            asm volatile("fence.mbarrier_init.release.cluster;" ::: "memory");
            if (cta < kAttn) { mbar_expect(FULL(0), SLOT); tma3d(sb, &tm_wq, 64 * cta, 0, 0, FULL(0)); }
#pragma unroll
            for (int s = 1; s < NSLOT; s++) mbar_init(FULL(s), 1);
#pragma unroll
            for (int s = 0; s < NSLOT; s++) mbar_init(EMPTY(s), cta < kAttn ? 8 : 1);
            asm volatile("fence.mbarrier_init.release.cluster;" ::: "memory");
        }
        __syncwarp();
        if (cta < kAttn) { if (lane >= 1 && lane < NSLOT) mbar_expect(FULL(lane), SLOT); }
        else if (lane < 10) mbar_expect(MFULL(lane), lane < 8 ? SLOT / 2 : SLOT);
    }
    if (t == 64) {
#pragma unroll
        for (int i = 0; i < 4; i++) mbar_init(XBAR(i), 1);
        asm volatile("fence.mbarrier_init.release.cluster;" ::: "memory");
        mbar_expect(XBAR(0), 1024);
        mbar_expect(XBAR(1), 128);
        mbar_expect(XBAR(2), cta < kAttn ? 2048 : 128);
        mbar_expect(XBAR(3), 2048);
    }
    __syncwarp();
    cluster_arrive();

    if (cta < kAttn) {
        const int g = cl, b = r >> 2, j = r & 3;
        if (w == 9) {
            bar_arrive(0, kThreads);
        } else if (w == 8) {
            bar_arrive(0, kThreads);
            if (lane == 0) {
                const int kvrow = (b * 8 + g) * 8192 + 6144 + 512 * j;
                uint32_t dst = sb + SLOT, fb = FULL(1), fend = FULL(NSLOT), ph = 1;
                asm volatile("" : "+r"(dst), "+r"(fb), "+r"(fend));
                int i = 1;
                const uint32_t pace = p.pace;
                uint32_t due = ns0 - p.lead + ((cta * 37) & 63) * p.stag;
                auto run = [&](const CUtensorMap* m, int c0, int c1, int step, int n) {
#pragma unroll 1
                    for (; n > 0; n--, i++, c1 += step) {
                        if (i >= NSLOT) { mbar_wait(fb + 128, ph); mbar_expect(fb, SLOT); }
                        due += pace;
                        spin_until(due);
                        tma3d(dst, m, c0, c1, 0, fb);
                        dst += SLOT; fb += 8;
                        if (fb == fend) { fb -= 8 * NSLOT; dst -= SLOT * NSLOT; ph ^= 1; }
                    }
                };
                run(&tm_wq, 64 * cta, 128, 128, 3);
                run(&tm_k, 0, kvrow, 64, 8);
                run(&tm_v, 0, kvrow, 64, 8);
                run(&tm_wo, 64 * r, 512 * g, 128, 4);
                PROF(8);
                PROF_DUMP();
            }
            __syncwarp();
            cluster_wait();
        } else {
            if (w < 2) {
                const uint4* xp = reinterpret_cast<const uint4*>(p.x + w * 512 + lane * 16);
                const uint4 xa = __ldg(xp), xb = __ldg(xp + 1);
                const uint32_t u[8] = {xa.x, xa.y, xa.z, xa.w, xb.x, xb.y, xb.z, xb.w};
                float v[16], f[16];
#pragma unroll
                for (int i = 0; i < 8; i++) { v[2 * i] = bflo(u[i]); v[2 * i + 1] = bfhi(u[i]); }
#pragma unroll
                for (int i = 0; i < 16; i++) f[i] = v[i];
                float sm = tree_sum(f);
#pragma unroll
                for (int o = 16; o; o >>= 1) sm += __shfl_xor_sync(0xffffffffu, sm, o);
                const float mean = sm * (1.f / 512.f);
#pragma unroll
                for (int i = 0; i < 16; i++) { const float d = v[i] - mean; f[i] = d * d; }
                float sq = tree_sum(f);
#pragma unroll
                for (int o = 16; o; o >>= 1) sq += __shfl_xor_sync(0xffffffffu, sq, o);
                const float mb = bfr(mean), rden = ln_rden(sq * (1.f / 512.f));
                uint32_t o[8];
#pragma unroll
                for (int i = 0; i < 8; i++) {
                    const uint32_t c = pack2(v[2 * i] - mb, v[2 * i + 1] - mb);
                    o[i] = pack2(bflo(c) * rden, bfhi(c) * rden);
                }
                const uint32_t d = mb_ + A_XN + w * 1040 + lane * 32;
                sts4u(d, o[0], o[1], o[2], o[3]);
                sts4u(d + 16, o[4], o[5], o[6], o[7]);
            }
            unsigned ep;
            asm volatile("ld.relaxed.gpu.global.u32 %0, [%1];" : "=r"(ep) : "l"(p.epoch) : "memory");
            uint2 xr;
            asm volatile("ld.global.nc.v2.u32 {%0,%1}, [%2];" : "=r"(xr.x), "=r"(xr.y) : "l"(p.x + (hq >> 1) * 512 + 16 * (cta >> 1) + 4 * (cta & 1) + (hq & 1) * 8));
            const int mt = w & 3, hp = w >> 2, h0 = 2 * (hq & 1);
            const int mi = lane >> 3, rr = (lane & 7) + (mi >> 1) * 8;
            const uint32_t act_off = (lane & 7) * 1040 + hp * 128 + mi * 16;
            const uint32_t wt_off = sb + (64 * hp + rr) * 128 + (((2 * mt + (mi & 1)) ^ (rr & 7)) << 4);
            uint32_t gp_st = mb_ + A_GP + hp * 512 + (16 * mt + grp) * 4;
            constexpr float L2E = 1.4426950408889634f;
            bar_sync(0, kThreads);
            PROF(0);
            {
                float acc[2][4] = {};
#pragma unroll 1
                for (int i = 0; i < 4; i++) {
                    uint32_t bf[2][4];
                    ldsm4(bf[0], mb_ + A_XN + act_off + i * 256);
                    ldsm4(bf[1], mb_ + A_XN + act_off + i * 256 + 64);
                    mbar_wait(FULL(i), 0);
                    if (i == 0) PROF(2);
#pragma unroll
                    for (int k = 0; k < 4; k++) {
                        uint32_t a[4];
                        ldsm4t(a, wt_off + i * SLOT + k * 2048);
                        mma(acc[k & 1], a[0], a[1], a[2], a[3], bf[k >> 1][(k & 1) * 2], bf[k >> 1][(k & 1) * 2 + 1]);
                    }
                    __syncwarp();
                    if (lane == 0) mbar_arrive(EMPTY(i));
                }
                if (hq == 0) {
                    sts1(gp_st, acc[0][0] + acc[1][0]); sts1(gp_st + 256, acc[0][1] + acc[1][1]);
                    sts1(gp_st + 32, acc[0][2] + acc[1][2]); sts1(gp_st + 256 + 32, acc[0][3] + acc[1][3]);
                }
                cluster_wait();
                bar_sync(1, 256);
                if (w < 2) {
                    const int tg = t >> 3, pc = t & 7;
                    const uint32_t src = mb_ + A_GP + (tg >> 2) * 256 + pc * 32;
                    float u0[4], u1[4], v0[4], v1[4];
                    lds4(u0, src); lds4(u1, src + 16); lds4(v0, src + 512); lds4(v1, src + 512 + 16);
                    st_async4(mapa(mb_ + A_Q + (r >> 1) * 272 + (r & 1) * 128 + pc * 16, tg), pack2(u0[0] + v0[0], u0[1] + v0[1]),
                              pack2(u0[2] + v0[2], u0[3] + v0[3]), pack2(u1[0] + v1[0], u1[1] + v1[1]), pack2(u1[2] + v1[2], u1[3] + v1[3]),
                              mapa(XBAR(0), tg));
                }
            }
            if (w == 2) st_mail4(p.attn_part + g * 1024 + r * 128 + lane * 4, ep & 1);
            PROF(1);
            int s = 4, ph = 0;
            float sc[4][4] = {};
            {
                mbar_wait(XBAR(0), 0);
                uint32_t qf[4][4];
#pragma unroll
                for (int i = 0; i < 4; i++) ldsm4(qf[i], mb_ + A_Q + (lane & 7) * 272 + i * 64 + (lane >> 3) * 16);
                const int row = 16 * mt + (lane & 7) + ((lane >> 3) & 1) * 8;
                const uint32_t x0a = row * 128 + ((((lane >> 4) ^ (row & 7))) << 4);
#pragma unroll 1
                for (int c = 0; c < 8; c++) {
                    if ((c & 1) == hp) {
                        mbar_wait(FULL(s), ph);
                        float s0[4] = {}, s1[4] = {};
                        const uint32_t kb = sb + s * SLOT;
#pragma unroll
                        for (int ks = 0; ks < 8; ks++) {
                            uint32_t a[4];
                            ldsm4(a, kb + (ks >> 2) * 8192 + (x0a ^ ((ks & 3) << 5)));
                            if (ks & 1) mma(s1, a[0], a[1], a[2], a[3], qf[ks >> 1][2], qf[ks >> 1][3]);
                            else mma(s0, a[0], a[1], a[2], a[3], qf[ks >> 1][0], qf[ks >> 1][1]);
                        }
#pragma unroll
                        for (int k = 0; k < 3; k++)
#pragma unroll
                            for (int e = 0; e < 4; e++) sc[k][e] = sc[k + 1][e];
                        const uint32_t r1 = pack2(s0[0] + s1[0], s0[1] + s1[1]), r3 = pack2(s0[2] + s1[2], s0[3] + s1[3]);
                        const uint32_t r2 = pack2(bflo(r1) * 0.08838834764831845f, bfhi(r1) * 0.08838834764831845f);
                        const uint32_t r4 = pack2(bflo(r3) * 0.08838834764831845f, bfhi(r3) * 0.08838834764831845f);
                        sc[3][0] = bflo(r2); sc[3][1] = bfhi(r2); sc[3][2] = bflo(r4); sc[3][3] = bfhi(r4);
                        __syncwarp();
                        if (lane < 2) mbar_arrive(EMPTY(s));
                    }
                    if (++s == NSLOT) { s = 0; ph ^= 1; }
                }
            }
            PROF(3);
            {
                float m0 = fmaxf(fmaxf(fmaxf(sc[0][0], sc[1][0]), fmaxf(sc[2][0], sc[3][0])), fmaxf(fmaxf(sc[0][2], sc[1][2]), fmaxf(sc[2][2], sc[3][2])));
                float m1 = fmaxf(fmaxf(fmaxf(sc[0][1], sc[1][1]), fmaxf(sc[2][1], sc[3][1])), fmaxf(fmaxf(sc[0][3], sc[1][3]), fmaxf(sc[2][3], sc[3][3])));
#pragma unroll
                for (int o = 4; o <= 16; o <<= 1) {
                    m0 = fmaxf(m0, __shfl_xor_sync(0xffffffffu, m0, o));
                    m1 = fmaxf(m1, __shfl_xor_sync(0xffffffffu, m1, o));
                }
                if (lane < 2) { sts1(mb_ + A_WM + h0 * 32 + w * 4, m0); sts1(mb_ + A_WM + h0 * 32 + 32 + w * 4, m1); }
                bar_sync(1, 256);
                float a0[4], a1[4], b0[4], b1[4];
                lds4(a0, mb_ + A_WM + h0 * 32); lds4(a1, mb_ + A_WM + h0 * 32 + 16);
                lds4(b0, mb_ + A_WM + h0 * 32 + 32); lds4(b1, mb_ + A_WM + h0 * 32 + 48);
                m0 = fmaxf(fmaxf(fmaxf(a0[0], a0[1]), fmaxf(a0[2], a0[3])), fmaxf(fmaxf(a1[0], a1[1]), fmaxf(a1[2], a1[3])));
                m1 = fmaxf(fmaxf(fmaxf(b0[0], b0[1]), fmaxf(b0[2], b0[3])), fmaxf(fmaxf(b1[0], b1[1]), fmaxf(b1[2], b1[3])));
                const uint32_t pa = mb_ + A_P + h0 * 1040 + (64 * hp + 16 * mt + grp) * 2;
                float l0 = 0.f, l1 = 0.f;
#pragma unroll
                for (int i = 0; i < 4; i++) {
                    const float e0 = ex2((sc[i][0] - m0) * L2E), e1 = ex2((sc[i][1] - m1) * L2E);
                    const float e2 = ex2((sc[i][2] - m0) * L2E), e3 = ex2((sc[i][3] - m1) * L2E);
                    if (hq < 2) {
                        sts16(pa + i * 256, e0);
                        sts16(pa + i * 256 + 1040, e1);
                        sts16(pa + i * 256 + 16, e2);
                        sts16(pa + i * 256 + 1040 + 16, e3);
                    }
                    l0 += e0 + e2; l1 += e1 + e3;
                }
#pragma unroll
                for (int o = 4; o <= 16; o <<= 1) {
                    l0 += __shfl_xor_sync(0xffffffffu, l0, o);
                    l1 += __shfl_xor_sync(0xffffffffu, l1, o);
                }
                if (lane < 2) { sts1(mb_ + A_WS + h0 * 32 + w * 4, l0); sts1(mb_ + A_WS + h0 * 32 + 32 + w * 4, l1); }
                bar_sync(1, 256);
                if (w == 7) {
                    lds4(a0, mb_ + A_WS + h0 * 32); lds4(a1, mb_ + A_WS + h0 * 32 + 16);
                    lds4(b0, mb_ + A_WS + h0 * 32 + 32); lds4(b1, mb_ + A_WS + h0 * 32 + 48);
                    l0 = ((a0[0] + a0[1]) + (a0[2] + a0[3])) + ((a1[0] + a1[1]) + (a1[2] + a1[3]));
                    l1 = ((b0[0] + b0[1]) + (b0[2] + b0[3])) + ((b1[0] + b1[1]) + (b1[2] + b1[3]));
                    if (lane < 8) {
                        const uint32_t tgt = 4 * b + (lane >> 1);
                        st_async4(mapa(mb_ + A_ST + j * 32 + (lane & 1) * 16, tgt), __float_as_uint(m0), __float_as_uint(l0),
                                  __float_as_uint(m1), __float_as_uint(l1), mapa(XBAR(1), tgt));
                    }
                }
            }
            PROF(4);
            {
                float o0[4] = {}, o1[4] = {};
                const int ch = 2 * w + (mi & 1);
                const uint32_t voff = sb + (ch >> 3) * 8192 + rr * 128 + (((ch & 7) ^ (rr & 7)) << 4);
                const uint32_t poff = mb_ + A_P + (lane & 7) * 1040 + (lane >> 3) * 16;
#pragma unroll 1
                for (int c = 0; c < 8; c++) {
                    uint32_t pf[2][4];
                    ldsm4(pf[0], poff + c * 128);
                    ldsm4(pf[1], poff + c * 128 + 64);
                    mbar_wait(FULL(s), ph);
#pragma unroll
                    for (int ks = 0; ks < 4; ks++) {
                        uint32_t a[4];
                        ldsm4t(a, voff + s * SLOT + ks * 2048);
                        if (ks & 1) mma(o1, a[0], a[1], a[2], a[3], pf[ks >> 1][2], pf[ks >> 1][3]);
                        else mma(o0, a[0], a[1], a[2], a[3], pf[ks >> 1][0], pf[ks >> 1][1]);
                    }
                    __syncwarp();
                    if (lane == 0) mbar_arrive(EMPTY(s));
                    if (++s == NSLOT) { s = 0; ph ^= 1; }
                }
                PROF(5);
                if (hq < 2) {
                    const uint32_t d = mb_ + A_OP + h0 * 544 + (16 * w + grp) * 4;
                    sts1(d, o0[0] + o1[0]);
                    sts1(d + 544, o0[1] + o1[1]);
                    sts1(d + 32, o0[2] + o1[2]);
                    sts1(d + 544 + 32, o0[3] + o1[3]);
                }
            }
            if (w < 4) {
                mbar_wait(XBAR(1), 0);
                float f[4];
                {
                    float mm[4], ll[4];
#pragma unroll
                    for (int i = 0; i < 4; i++) { mm[i] = lds1(mb_ + A_ST + i * 32 + j * 8); ll[i] = lds1(mb_ + A_ST + i * 32 + j * 8 + 4); }
                    const float M = fmaxf(fmaxf(mm[0], mm[1]), fmaxf(mm[2], mm[3]));
#pragma unroll
                    for (int i = 0; i < 4; i++) f[i] = ex2((mm[i] - M) * L2E);
                    const float inv = rcp_((ll[0] * f[0] + ll[1] * f[1]) + (ll[2] * f[2] + ll[3] * f[3]));
#pragma unroll
                    for (int i = 0; i < 4; i++) f[i] *= inv;
                }
                bar_sync(1, 256);
                const uint4 v = lds4u(mb_ + A_OP + w * 544 + lane * 16);
                const uint32_t tgt = 4 * b + w;
                st_async4(mapa(mb_ + A_RS + j * 512 + lane * 16, tgt), v.x, v.y, v.z, v.w, mapa(XBAR(2), tgt));
                const int tg2 = t >> 4, pc = t & 15;
                const uint32_t da = mapa(mb_ + A_O + b * 1040 + j * 256 + pc * 16, tg2), db = mapa(XBAR(3), tg2);
                mbar_wait(XBAR(2), 0);
                float u[4][8];
#pragma unroll
                for (int i = 0; i < 4; i++) {
                    lds4(*reinterpret_cast<float(*)[4]>(&u[i][0]), mb_ + A_RS + i * 512 + pc * 32);
                    lds4(*reinterpret_cast<float(*)[4]>(&u[i][4]), mb_ + A_RS + i * 512 + pc * 32 + 16);
                }
                float o8[8];
#pragma unroll
                for (int k = 0; k < 8; k++) o8[k] = (u[0][k] * f[0] + u[1][k] * f[1]) + (u[2][k] * f[2] + u[3][k] * f[3]);
                st_async4(da, pack2(o8[0], o8[1]), pack2(o8[2], o8[3]), pack2(o8[4], o8[5]), pack2(o8[6], o8[7]), db);
            } else {
                bar_arrive(1, 256);
            }
            const uint32_t tag = (ep + 1) & 1;
            {
                float* pub = p.attn_part + g * 1024 + r * 128 + lane * 4;
                uint32_t oa = mb_ + A_O + act_off, gp_ld = mb_ + A_GP + lane * 16;
                asm volatile("" : "+l"(pub), "+r"(oa), "+r"(gp_ld), "+r"(gp_st));
                uint32_t wf[3][4][4];
#pragma unroll
                for (int c = 0; c < 3; c++) {
                    mbar_wait(FULL(s), ph);
#pragma unroll
                    for (int k = 0; k < 4; k++) ldsm4t(wf[c][k], wt_off + s * SLOT + k * 2048);
                    if (++s == NSLOT) { s = 0; ph ^= 1; }
                }
                uint32_t wl = wt_off + s * SLOT, fl = FULL(s);
                asm volatile("" : "+r"(wl), "+r"(fl));
                mbar_wait(XBAR(3), 0);
                PROF(6);
                uint32_t bf[4][2][4];
#pragma unroll
                for (int c = 0; c < 4; c++) { ldsm4(bf[c][0], oa + c * 256); ldsm4(bf[c][1], oa + c * 256 + 64); }
                float acc[4][4] = {};
#pragma unroll
                for (int c = 0; c < 3; c++)
#pragma unroll
                    for (int k = 0; k < 4; k++)
                        mma(acc[k], wf[c][k][0], wf[c][k][1], wf[c][k][2], wf[c][k][3], bf[c][k >> 1][(k & 1) * 2], bf[c][k >> 1][(k & 1) * 2 + 1]);
                mbar_wait(fl, ph);
                PROF(9);
#pragma unroll
                for (int k = 0; k < 4; k++) {
                    uint32_t a[4];
                    ldsm4t(a, wl + k * 2048);
                    mma(acc[k], a[0], a[1], a[2], a[3], bf[3][k >> 1][(k & 1) * 2], bf[3][k >> 1][(k & 1) * 2 + 1]);
                }
                if (hq == 0) {
                    sts1(gp_st, (acc[0][0] + acc[1][0]) + (acc[2][0] + acc[3][0]));
                    sts1(gp_st + 256, (acc[0][1] + acc[1][1]) + (acc[2][1] + acc[3][1]));
                    sts1(gp_st + 32, (acc[0][2] + acc[1][2]) + (acc[2][2] + acc[3][2]));
                    sts1(gp_st + 256 + 32, (acc[0][3] + acc[1][3]) + (acc[2][3] + acc[3][3]));
                }
                if (w == 2) {
                    bar_sync(1, 256);
                    float u[4], v[4];
                    lds4(u, gp_ld); lds4(v, gp_ld + 512);
                    exch_tag4(pub, u[0] + v[0], u[1] + v[1], u[2] + v[2], u[3] + v[3], tag);
                    PROFL(12);
                } else {
                    bar_arrive(1, 256);
                }
                PROF(7);
            }
            const uint32_t tmask = 0u - tag;
            {
                const int c0 = 16 * (cta >> 1) + 4 * (cta & 1);
                const float* src = w == 0 ? p.attn_part + grp * 1024 + (c0 >> 6) * 128 + (hq >> 1) * 64 + (c0 & 63) + (hq & 1) * 8
                                          : p.out_part + cl * 4096 + (8 * (w - 1) + grp) * 64 + r * 8 + 2 * hq;
                __nv_bfloat16* outp = p.out + c0 + hq;
                unsigned* epp = p.epoch;
                uint32_t fs = mb_ + A_RS + w * 64 + hq * 16;
                asm volatile("" : "+l"(outp), "+l"(epp), "+l"(src), "+r"(fs));
                float d4[4];
                if (w == 0) {
                    const uint4 v = poll_packet(src, tmask);
                    d4[0] = __uint_as_float(v.x); d4[1] = __uint_as_float(v.y); d4[2] = __uint_as_float(v.z); d4[3] = __uint_as_float(v.w);
                } else {
                    uint2 v;
                    int it = 0;
                    do { v = ld_poll2(src); } while (__any_sync(0xffffffffu, ((v.x ^ tmask) | (v.y ^ tmask)) & 1u) && ++it < POLL_LIMIT);
                    d4[0] = bfhi(v.x); d4[1] = bflo(v.x); d4[2] = bfhi(v.y); d4[3] = bflo(v.y);
                }
#pragma unroll
                for (int o = 4; o <= 16; o <<= 1) {
#pragma unroll
                    for (int i = 0; i < 4; i++) d4[i] += __shfl_xor_sync(0xffffffffu, d4[i], o);
                }
                if (w) {
                    if (lane < 4) sts4u(fs, __float_as_uint(d4[0]), __float_as_uint(d4[1]), __float_as_uint(d4[2]), __float_as_uint(d4[3]));
                    bar_arrive(3, 256);
                } else {
                    if (lane < 4) {
                        const uint32_t d = mb_ + A_RS + (hq & 1) * 8 + (hq >> 1) * 4;
                        sts1(d, bfr(bflo(xr.x) + bfr(d4[0])));
                        sts1(d + 16, bfr(bfhi(xr.x) + bfr(d4[1])));
                        sts1(d + 32, bfr(bflo(xr.y) + bfr(d4[2])));
                        sts1(d + 48, bfr(bfhi(xr.y) + bfr(d4[3])));
                    }
                    PROF(10);
                    bar_sync(3, 256);
                    float u[8][4];
#pragma unroll
                    for (int i = 0; i < 8; i++) lds4(u[i], fs + i * 64);
#pragma unroll
                    for (int k = 0; k < 4; k++) d4[k] = u[0][k] + bfr(((u[1][k] + u[2][k]) + (u[3][k] + u[4][k])) + ((u[5][k] + u[6][k]) + u[7][k]));
                    if (lane < 4) {
                        outp[0] = __float2bfloat16_rn(d4[0]);
                        outp[512] = __float2bfloat16_rn(d4[1]);
                        outp[8] = __float2bfloat16_rn(d4[2]);
                        outp[520] = __float2bfloat16_rn(d4[3]);
                        if (cta == 0 && lane == 0) *epp = ep + 1;
                    }
                    PROF(11);
                }
            }
            PROF_DUMP();
        }
    } else {
        const int m = cta - kAttn;
        unsigned ep;
        asm volatile("ld.relaxed.gpu.global.u32 %0, [%1];" : "=r"(ep) : "l"(p.epoch) : "memory");
        if (w == 9) {
            bar_sync(0, kThreads);
            if (lane == 0) {
#pragma unroll 1
                for (int i = 0; i < 10; i++) {
                    spin_until(ns0 + p.mlp_t0 + (i < 8 ? i : 2 * i - 8) * p.mlp_dt + ((m * 37) & 63) * p.mlp_stag);
                    if (i < 8) tma2d(sb + (i & 1) * 32768 + (i >> 1) * 8192, (i & 1) ? &tm_u : &tm_g, 32 * m, 128 * (i >> 1), MFULL(i));
                    else tma3d(sb + M_DOWN + (i - 8) * 16384, &tm_d, 0, 32 * m, 4 * (i - 8), MFULL(i));
                }
            }
        } else if (w == 8) {
            bar_arrive(0, kThreads);
            uint2 xv;
            asm volatile("ld.global.nc.v2.u32 {%0,%1}, [%2];" : "=r"(xv.x), "=r"(xv.y) : "l"(p.x + (lane >> 4) * 512 + 64 * r + (lane & 15) * 4));
            cluster_wait();
            const uint32_t dst = mb_ + M_H + (lane >> 4) * 1040 + 128 * r + ((lane & 15) >> 1) * 16;
            uint32_t da[4], db[4], gl = mb_ + M_G3 + lane * 16;
#pragma unroll
            for (int i = 0; i < 4; i++) { da[i] = mapa(dst, 2 * i + (lane & 1)); db[i] = mapa(XBAR(3), 2 * i + (lane & 1)); }
            uint32_t sl = mb_ + M_SP + (lane >> 4) * 64;
            uint32_t sa = mapa(sl + r * 8, lane & 7), sbar = mapa(XBAR(2), lane & 7);
            float xf[4] = {bflo(xv.x), bfhi(xv.x), bflo(xv.y), bfhi(xv.y)};
            asm volatile("" : "+r"(gl), "+r"(sl), "+r"(sa), "+r"(sbar), "+f"(xf[0]), "+f"(xf[1]), "+f"(xf[2]), "+f"(xf[3]));
            bar_sync(3, 288);
            float u[8][4], a4[4];
#pragma unroll
            for (int i = 0; i < 8; i++) lds4(u[i], gl + i * 512);
#pragma unroll
            for (int k = 0; k < 4; k++) a4[k] = xf[k] + bfr(((u[0][k] + u[1][k]) + (u[2][k] + u[3][k])) + ((u[4][k] + u[5][k]) + (u[6][k] + u[7][k])));
            const uint32_t hw0 = pack2(a4[0], a4[1]), hw1 = pack2(a4[2], a4[3]);
            const uint32_t ow0 = __shfl_xor_sync(0xffffffffu, hw0, 1), ow1 = __shfl_xor_sync(0xffffffffu, hw1, 1);
            const bool odd = lane & 1;
            const uint32_t e0 = odd ? ow0 : hw0, e1 = odd ? ow1 : hw1, e2 = odd ? hw0 : ow0, e3 = odd ? hw1 : ow1;
#pragma unroll
            for (int i = 0; i < 4; i++) st_async4(da[i], e0, e1, e2, e3, db[i]);
            PROF(9);
            {
                const float h0 = bflo(hw0), h1 = bfhi(hw0), h2 = bflo(hw1), h3 = bfhi(hw1);
                float s1 = (h0 + h1) + (h2 + h3), s2 = fmaf(h0, h0, h1 * h1) + fmaf(h2, h2, h3 * h3);
#pragma unroll
                for (int o = 8; o; o >>= 1) { s1 += __shfl_xor_sync(0xffffffffu, s1, o); s2 += __shfl_xor_sync(0xffffffffu, s2, o); }
                if (!(lane & 8))
                    asm volatile("st.async.weak.shared::cluster.mbarrier::complete_tx::bytes.v2.b32 [%0], {%1,%2}, [%3];"
                                 ::"r"(sa), "r"(__float_as_uint(s1)), "r"(__float_as_uint(s2)), "r"(sbar) : "memory");
                mbar_wait(XBAR(2), 0);
                float u0[4], u1[4], u2[4], u3[4];
                lds4(u0, sl); lds4(u1, sl + 16); lds4(u2, sl + 32); lds4(u3, sl + 48);
                const float mean = (((u0[0] + u0[2]) + (u1[0] + u1[2])) + ((u2[0] + u2[2]) + (u3[0] + u3[2]))) * (1.f / 512.f);
                const float msq = (((u0[1] + u0[3]) + (u1[1] + u1[3])) + ((u2[1] + u2[3]) + (u3[1] + u3[3]))) * (1.f / 512.f);
                const float var = fmaxf(fmaf(-mean, mean, msq), 0.f);
                if ((lane & 15) == 0) sts2(mb_ + M_ST + (lane >> 4) * 8, bfr(mean), ln_rden(var));
            }
            bar_arrive(2, 288);
            PROF(10);
            PROF_DUMP();
        } else {
            if (t < 32) asm volatile("st.shared.u32 [%0], %1;" ::"r"(mb_ + M_CS + (t & 31) * 4), "r"(0x3f803f80u) : "memory");
            bar_sync(0, kThreads);
            cluster_wait();
            const int mi = lane >> 3, rr = (lane & 7) + (mi >> 1) * 8;
            float* dout = p.out_part + w * 4096 + m * 64 + hq * 16 + 2 * grp;
            const int bb = (w >> 1) & 1, mat = lane >> 4, col = (w & 1) * 16 + (lane & 15);
            uint32_t tag = (ep + 1) & 1, trnd = (ep & 1) << 16;
            uint32_t ha = grp < 6 ? mb_ + M_H + (grp & 1) * 1040 + w * 128 + hq * 4 : mb_ + M_CS + hq * 4;
            uint32_t pst = hq == 3 ? mb_ + M_CSP + w * 256 + grp * 4 : mb_ + M_PART + w * 768 + ((hq >> 1) * 48 + (hq & 1) * 16 + grp) * 4;
            uint32_t pst2 = hq == 3 ? pst + 128 : pst + 256, po1 = hq == 3 ? 32 : 384, po2 = hq == 3 ? 64 : 32;
            uint32_t pld = mb_ + M_PART + bb * 384 + (mat * 48 + col) * 4, cld = mb_ + M_CSP + (mat * 32 + col) * 4;
            uint32_t sld = mb_ + M_ST + bb * 8, hst = mb_ + M_HH + bb * 80 + col * 2, hld = mb_ + M_HH + (grp & 1) * 80 + hq * 4;
            uint32_t dn = sb + M_DOWN + w * 4096 + rr * 128 + (((mi & 1) ^ (rr & 7)) << 4), xb = XBAR(3);
            asm volatile("" : "+l"(dout), "+r"(tag), "+r"(trnd), "+r"(ha), "+r"(pst), "+r"(pst2), "+r"(po1), "+r"(po2), "+r"(pld), "+r"(cld), "+r"(sld), "+r"(hst), "+r"(hld), "+r"(dn), "+r"(xb));
            uint32_t wf[4][4][4];
            const uint32_t fa = MFULL(w & 6), fb = fa + 8;
            bool ready;
            {
                int it = 0;
                do { ready = mbar_test(fa, 0) && mbar_test(fb, 0); } while (!ready && nsclock() - ns0 < (uint32_t)p.poll_t0 && ++it < SPIN_LIMIT);
            }
            ready = __all_sync(0xffffffffu, ready);
            auto stage_gu = [&]() {
                mbar_wait(fa, 0);
                mbar_wait(fb, 0);
#pragma unroll
                for (int tl = 0; tl < 4; tl++)
#pragma unroll
                    for (int ks = 0; ks < 4; ks++) {
                        const int row = 64 * w + 16 * ks + rr;
                        const int ch = 2 * (tl & 1) + (mi & 1);
                        ldsm4t(wf[tl][ks], sb + (tl >> 1) * 32768 + row * 64 + ((ch ^ ((row >> 1) & 3)) << 4));
                    }
                PROF(0);
            };
            if (ready) stage_gu();
            {
                spin_until(ns0 + p.poll_t0);
                const uint4 v = poll_packet(p.attn_part + w * 1024 + r * 128 + lane * 4, 0u - tag);
                sts4u(mb_ + M_G3 + w * 512 + lane * 16, v.x, v.y, v.z, v.w);
                bar_arrive(3, 288);
            }
            if (!ready) stage_gu();
            PROF(4);
            uint32_t df[4][2][4];
            const uint32_t fd = MFULL(8 + (w >> 2));
            bool early = false;
            if (NSLOT > 6) {
                int it = 0;
                do { early = mbar_test(fd, 0); } while (!early && !mbar_test(xb, 0) && ++it < MBAR_LIMIT);
                early = __all_sync(0xffffffffu, early);
            }
            auto stage_dn = [&]() {
                mbar_wait(fd, 0);
#pragma unroll
                for (int tl = 0; tl < 4; tl++)
#pragma unroll
                    for (int ks = 0; ks < 2; ks++) ldsm4t(df[tl][ks], (dn ^ (tl << 5)) + ks * 2048);
            };
            if (early) stage_dn();
            {
                {
                    mbar_wait(xb, 0);
                    PROF(1);
                    uint32_t hf[8];
#pragma unroll
                    for (int k = 0; k < 8; k++) hf[k] = lds1u(ha + k * 16);
                    float c[4][4] = {};
#pragma unroll
                    for (int ks = 0; ks < 4; ks++)
#pragma unroll
                        for (int tl = 0; tl < 4; tl++)
                            mma(c[tl], wf[tl][ks][0], wf[tl][ks][1], wf[tl][ks][2], wf[tl][ks][3], hf[2 * ks], hf[2 * ks + 1]);
                    const bool h3 = hq == 3;
                    const float v0 = hq == 0 ? c[0][0] : hq == 1 ? c[1][0] : hq == 2 ? c[2][0] : c[0][0];
                    const float v1 = hq == 0 ? c[0][1] : hq == 1 ? c[1][1] : hq == 2 ? c[2][1] : c[0][2];
                    const float v2 = hq == 0 ? c[0][2] : hq == 1 ? c[1][2] : hq == 2 ? c[2][2] : c[1][0];
                    const float v3 = hq == 0 ? c[0][3] : hq == 1 ? c[1][3] : hq == 2 ? c[2][3] : c[1][2];
                    sts1(pst, v0); sts1(pst + po1, v1); sts1(pst + po2, v2); sts1(pst + po1 + po2, v3);
                    if (hq == 0 || h3) {
                        sts1(pst2, h3 ? c[2][0] : c[3][0]); sts1(pst2 + po1, h3 ? c[2][2] : c[3][1]);
                        sts1(pst2 + po2, h3 ? c[3][0] : c[3][2]); sts1(pst2 + po1 + po2, h3 ? c[3][2] : c[3][3]);
                    }
                    if (w < 4) {
                        bar_sync(2, 288);
                        float f[8], cf[8];
#pragma unroll
                        for (int i = 0; i < 8; i++) f[i] = lds1(pld + i * 768);
#pragma unroll
                        for (int i = 0; i < 8; i++) cf[i] = lds1(cld + i * 256);
                        const float mean = lds1(sld), rs = lds1(sld + 4);
                        const float g = bfr(fmaf(-mean, tree_sum(cf), tree_sum(f)) * rs);
                        const float u = __shfl_xor_sync(0xffffffffu, g, 16);
                        const float e = ex2(g * fmaf(g * g, -0.10294324f, -2.3022082f));
                        const float ge = bfr(g * rcp_(1.f + e));
                        if (lane < 16) sts16(hst, ge * u);
                        PROF(2);
                    } else {
                        bar_arrive(2, 288);
                    }
                }
            }
            if (!early) stage_dn();
            PROF(5);
            bar_sync(1, 256);
            uint32_t hf[4];
#pragma unroll
            for (int k = 0; k < 4; k++) hf[k] = lds1u(hld + k * 16);
            float c[4][4] = {};
#pragma unroll
            for (int ks = 0; ks < 2; ks++)
#pragma unroll
                for (int tl = 0; tl < 4; tl++) mma(c[tl], df[tl][ks][0], df[tl][ks][1], df[tl][ks][2], df[tl][ks][3], hf[2 * ks], hf[2 * ks + 1]);
            {
                float v[4];
#pragma unroll
                for (int k = 0; k < 4; k++) {
                    const float lo = (hq & 1) ? c[1][k] : c[0][k], hi = (hq & 1) ? c[3][k] : c[2][k];
                    v[k] = (hq & 2) ? hi : lo;
                }
                st_mail2(dout, pack_tag(v[0], v[1], tag, trnd), pack_tag(v[2], v[3], tag, trnd));
            }
            PROF(3);
            PROF_DUMP();
        }
    }
}

typedef CUresult (*EncodeFn)(CUtensorMap*, CUtensorMapDataType, cuuint32_t, void*, const cuuint64_t*, const cuuint64_t*,
                             const cuuint32_t*, const cuuint32_t*, CUtensorMapInterleave, CUtensorMapSwizzle,
                             CUtensorMapL2promotion, CUtensorMapFloatOOBfill);

void make_map(EncodeFn enc, CUtensorMap* m, const void* ptr, int rank, const cuuint64_t* dims, const cuuint64_t* strides,
              const cuuint32_t* box, CUtensorMapSwizzle sw) {
    const cuuint32_t es[3] = {1, 1, 1};
    enc(m, CU_TENSOR_MAP_DATA_TYPE_BFLOAT16, rank, const_cast<void*>(ptr), dims, strides, box, es, CU_TENSOR_MAP_INTERLEAVE_NONE, sw,
        CU_TENSOR_MAP_L2_PROMOTION_L2_128B, CU_TENSOR_MAP_FLOAT_OOB_FILL_NONE);
}

}

#define SCHED 330, 240, 5, 7700, 170, 3, 9000
static int g_sched[7] = {SCHED};
static int g_small = -1;

extern "C" void kernel_launch(void* const* d_in, const int* in_sizes, int n_in, void* d_out, int out_size) {
    (void)in_sizes; (void)n_in; (void)out_size;
    static EncodeFn enc = nullptr;
    static void *a_epoch, *a_mail;
    if (!enc) {
        void* fn = nullptr;
        cudaDriverEntryPointQueryResult qr;
        cudaGetDriverEntryPoint("cuTensorMapEncodeTiled", &fn, cudaEnableDefault, &qr);
        enc = (EncodeFn)fn;
        cudaFuncSetAttribute(fused_decode<kBig>, cudaFuncAttributeMaxDynamicSharedMemorySize, smem_bytes(kBig));
        cudaFuncSetAttribute(fused_decode<kSmall>, cudaFuncAttributeMaxDynamicSharedMemorySize, smem_bytes(kSmall));
        cudaGetSymbolAddress(&a_epoch, g_epoch);
        cudaGetSymbolAddress(&a_mail, g_mail);
    }
    CUtensorMap tq, tk, tv, to, tg, tu, td;
    {
        const cuuint64_t d[3] = {4096, 512, 1}, s[2] = {8192, 4194304}; const cuuint32_t bx[3] = {64, 128, 1};
        make_map(enc, &tq, d_in[3], 3, d, s, bx, CU_TENSOR_MAP_SWIZZLE_128B);
    }
    {
        const cuuint64_t d[3] = {64, 131072, 2}, s[2] = {256, 128}; const cuuint32_t bx[3] = {64, 64, 2};
        make_map(enc, &tk, d_in[1], 3, d, s, bx, CU_TENSOR_MAP_SWIZZLE_128B);
        make_map(enc, &tv, d_in[2], 3, d, s, bx, CU_TENSOR_MAP_SWIZZLE_128B);
    }
    {
        const cuuint64_t d[3] = {512, 4096, 1}, s[2] = {1024, 4194304}; const cuuint32_t bx[3] = {64, 128, 1};
        make_map(enc, &to, d_in[4], 3, d, s, bx, CU_TENSOR_MAP_SWIZZLE_128B);
    }
    {
        const cuuint64_t d[2] = {1792, 512}, s[1] = {3584}; const cuuint32_t bx[2] = {32, 128};
        make_map(enc, &tg, d_in[6], 2, d, s, bx, CU_TENSOR_MAP_SWIZZLE_64B);
        make_map(enc, &tu, d_in[7], 2, d, s, bx, CU_TENSOR_MAP_SWIZZLE_64B);
    }
    {
        const cuuint64_t d[3] = {64, 1792, 8}, s[2] = {1024, 128}; const cuuint32_t bx[3] = {64, 32, 4};
        make_map(enc, &td, d_in[8], 3, d, s, bx, CU_TENSOR_MAP_SWIZZLE_128B);
    }
    Params p;
    p.x = (const __nv_bfloat16*)d_in[0];
    p.out = (__nv_bfloat16*)d_out;
    p.epoch = (unsigned*)a_epoch;
    p.attn_part = (float*)a_mail;
    p.out_part = p.attn_part + 8 * 1024;
    p.pace = g_sched[0]; p.lead = g_sched[1]; p.stag = g_sched[2]; p.mlp_t0 = g_sched[3]; p.mlp_dt = g_sched[4];
    p.mlp_stag = g_sched[5]; p.poll_t0 = g_sched[6];
    cudaLaunchConfig_t cfg = {};
    cfg.gridDim = dim3(kCtas);
    cfg.blockDim = dim3(kThreads);
    cfg.stream = cudaStreamPerThread;
    cudaLaunchAttribute at[1];
    at[0].id = cudaLaunchAttributeClusterDimension;
    at[0].val.clusterDim.x = 8; at[0].val.clusterDim.y = 1; at[0].val.clusterDim.z = 1;
    cfg.attrs = at;
    cfg.numAttrs = 1;
    if (g_small < 0) {
        int n = 0;
        cfg.dynamicSmemBytes = smem_bytes(kBig);
        cudaError_t e = cudaOccupancyMaxActiveClusters(&n, fused_decode<kBig>, &cfg);
        g_small = (e != cudaSuccess || n < kCtas / 8) ? 1 : 0;
        (void)cudaGetLastError();
    }
    if (g_small) {
        cfg.dynamicSmemBytes = smem_bytes(kSmall);
        cudaLaunchKernelEx(&cfg, fused_decode<kSmall>, tq, tk, tv, to, tg, tu, td, p);
    } else {
        cfg.dynamicSmemBytes = smem_bytes(kBig);
        cudaLaunchKernelEx(&cfg, fused_decode<kBig>, tq, tk, tv, to, tg, tu, td, p);
    }
}
```

```cpp
#include <cuda_runtime.h>
#include <cuda_bf16.h>
#include <cuda.h>
#include <stdint.h>

namespace {

constexpr int kAttn = 64, kMlp = 56, kCtas = kAttn + kMlp;
constexpr int SLOT = 16384;
constexpr int kBig = 13, kSmall = 6;
constexpr int A_XN = 0;
constexpr int A_O = A_XN + 2080;
constexpr int A_Q = A_O + 2080;
constexpr int A_P = A_Q + 1088;
constexpr int A_RS = A_P + 4160;
constexpr int A_OP = A_RS + 2048;
constexpr int A_ST = A_OP + 2176;
constexpr int A_WM = A_ST + 128;
constexpr int A_WS = A_WM + 128;
constexpr int A_GP = A_WS + 128;
constexpr int A_HH = A_XN;
constexpr int A_FIN = A_RS;
constexpr int A_HS = A_OP;
constexpr int A_END = A_GP + 1024;
constexpr int M_H = 0;
constexpr int M_PART = M_H + 2080;
constexpr int M_CSP = M_PART + 6144;
constexpr int M_CS = M_CSP + 2048;
constexpr int M_HH = M_CS + 256;
constexpr int M_ST = M_HH + 160;
constexpr int M_G3 = M_ST + 16;
constexpr int M_SP = M_G3 + 4096;
constexpr int M_END = M_SP + 128;
constexpr int OFF_BAR = ((A_END > M_END ? A_END : M_END) + 15) / 16 * 16;
constexpr int OFF_PROF = OFF_BAR + 37 * 8 + 8;
constexpr int MISC_BYTES = OFF_PROF + 64;
constexpr int kThreads = 320;
constexpr int smem_bytes(int nslot) { return nslot * SLOT + MISC_BYTES + 1024; }

constexpr int POLL_LIMIT = 200000;
constexpr int MBAR_LIMIT = 20000000;
constexpr int SPIN_LIMIT = 2000000;

struct Params {
    const __nv_bfloat16* x;
    __nv_bfloat16* out;
    unsigned* epoch;
    float* attn_part;
    float* hh_mail;
    int pace, lead, stag, mlp_t0, mlp_dt, mlp_stag, poll_t0, dn_gap;
};

__device__ unsigned g_epoch;
constexpr int kHhStride = 1056;
__device__ __align__(1024) float g_mail[8 * 1024 + 112 * kHhStride];
#define PROF(i) do {} while (0)
#define PROF_DUMP() do {} while (0)
#define PROFL(i) do {} while (0)
__device__ __forceinline__ uint32_t nsclock() { uint32_t c; asm volatile("mov.u32 %0, %%globaltimer_lo;" : "=r"(c) :: "memory"); return c; }
__device__ __forceinline__ uint32_t s2u(const void* p) { return (uint32_t)__cvta_generic_to_shared(p); }
__device__ __forceinline__ void mbar_init(uint32_t a, int c) { asm volatile("mbarrier.init.shared::cta.b64 [%0], %1;" ::"r"(a), "r"(c) : "memory"); }
__device__ __forceinline__ void mbar_expect(uint32_t a, uint32_t b) { asm volatile("mbarrier.arrive.expect_tx.shared::cta.b64 _, [%0], %1;" ::"r"(a), "r"(b) : "memory"); }
__device__ __forceinline__ void mbar_arrive(uint32_t a) { asm volatile("mbarrier.arrive.shared::cta.b64 _, [%0];" ::"r"(a) : "memory"); }
__device__ __forceinline__ void mbar_wait(uint32_t a, uint32_t ph) {
    uint32_t ok; int it = 0;
    do {
        asm volatile("{ .reg .pred p; mbarrier.try_wait.parity.shared::cta.b64 p, [%1], %2; selp.u32 %0, 1, 0, p; }" : "=r"(ok) : "r"(a), "r"(ph) : "memory");
    } while (!ok && ++it < MBAR_LIMIT);
}
__device__ __forceinline__ bool mbar_test(uint32_t a, uint32_t ph) {
    uint32_t ok;
    asm volatile("{ .reg .pred p; mbarrier.test_wait.parity.shared::cta.b64 p, [%1], %2; selp.u32 %0, 1, 0, p; }" : "=r"(ok) : "r"(a), "r"(ph) : "memory");
    return ok;
}
__device__ __forceinline__ void tma2d(uint32_t dst, const CUtensorMap* m, int c0, int c1, uint32_t bar) {
    asm volatile("cp.async.bulk.tensor.2d.shared::cluster.global.mbarrier::complete_tx::bytes [%0], [%1, {%3, %4}], [%2];"
                 ::"r"(dst), "l"(m), "r"(bar), "r"(c0), "r"(c1) : "memory");
}
__device__ __forceinline__ void tma3d(uint32_t dst, const CUtensorMap* m, int c0, int c1, int c2, uint32_t bar) {
    asm volatile("cp.async.bulk.tensor.3d.shared::cluster.global.mbarrier::complete_tx::bytes [%0], [%1, {%3, %4, %5}], [%2];"
                 ::"r"(dst), "l"(m), "r"(bar), "r"(c0), "r"(c1), "r"(c2) : "memory");
}
__device__ __forceinline__ uint32_t mapa(uint32_t a, uint32_t rank) { uint32_t r; asm("mapa.shared::cluster.u32 %0, %1, %2;" : "=r"(r) : "r"(a), "r"(rank)); return r; }
__device__ __forceinline__ void st_async4(uint32_t dst, uint32_t a, uint32_t b, uint32_t c, uint32_t d, uint32_t bar) {
    asm volatile("st.async.weak.shared::cluster.mbarrier::complete_tx::bytes.v4.b32 [%0], {%1,%2,%3,%4}, [%5];"
                 ::"r"(dst), "r"(a), "r"(b), "r"(c), "r"(d), "r"(bar) : "memory");
}
__device__ __forceinline__ void ldsm4(uint32_t (&r)[4], uint32_t a) {
    asm volatile("ldmatrix.sync.aligned.m8n8.x4.shared.b16 {%0,%1,%2,%3}, [%4];" : "=r"(r[0]), "=r"(r[1]), "=r"(r[2]), "=r"(r[3]) : "r"(a) : "memory");
}
__device__ __forceinline__ void ldsm4t(uint32_t (&r)[4], uint32_t a) {
    asm volatile("ldmatrix.sync.aligned.m8n8.x4.trans.shared.b16 {%0,%1,%2,%3}, [%4];" : "=r"(r[0]), "=r"(r[1]), "=r"(r[2]), "=r"(r[3]) : "r"(a) : "memory");
}
__device__ __forceinline__ void mma(float (&c)[4], uint32_t a0, uint32_t a1, uint32_t a2, uint32_t a3, uint32_t b0, uint32_t b1) {
    asm volatile("mma.sync.aligned.m16n8k16.row.col.f32.bf16.bf16.f32 {%0,%1,%2,%3}, {%4,%5,%6,%7}, {%8,%9}, {%0,%1,%2,%3};"
                 : "+f"(c[0]), "+f"(c[1]), "+f"(c[2]), "+f"(c[3]) : "r"(a0), "r"(a1), "r"(a2), "r"(a3), "r"(b0), "r"(b1));
}
__device__ __forceinline__ void bar_sync(int id, int n) { asm volatile("bar.sync %0, %1;" ::"r"(id), "r"(n) : "memory"); }
__device__ __forceinline__ void bar_arrive(int id, int n) { asm volatile("bar.arrive %0, %1;" ::"r"(id), "r"(n) : "memory"); }
__device__ __forceinline__ void cluster_arrive() { asm volatile("barrier.cluster.arrive.relaxed.aligned;" ::: "memory"); }
__device__ __forceinline__ void cluster_wait() { asm volatile("barrier.cluster.wait.acquire.aligned;" ::: "memory"); }
__device__ __forceinline__ uint32_t pack2(float lo, float hi) { uint32_t r; asm("cvt.rn.bf16x2.f32 %0, %1, %2;" : "=r"(r) : "f"(hi), "f"(lo)); return r; }
__device__ __forceinline__ float bfr(float v) { return __uint_as_float(pack2(0.f, v)); }
__device__ __forceinline__ float bflo(uint32_t v) { return __uint_as_float(v << 16); }
__device__ __forceinline__ float bfhi(uint32_t v) { return __uint_as_float(v & 0xffff0000u); }
__device__ __forceinline__ float ex2(float v) { float r; asm("ex2.approx.ftz.f32 %0, %1;" : "=f"(r) : "f"(v)); return r; }
__device__ __forceinline__ uint4 ld_poll(const float* p) {
    uint4 v;
    asm volatile("ld.relaxed.gpu.global.v4.u32 {%0,%1,%2,%3}, [%4];" : "=r"(v.x), "=r"(v.y), "=r"(v.z), "=r"(v.w) : "l"(p) : "memory");
    return v;
}
__device__ __forceinline__ void st_mail4(float* p, uint32_t v) {
    asm volatile("st.relaxed.gpu.global.v4.u32 [%0], {%1,%1,%1,%1};" ::"l"(p), "r"(v) : "memory");
}
__device__ __forceinline__ void exch_tag4(float* p, float a, float b, float c, float d, uint32_t tag) {
    const uint32_t x = (__float_as_uint(a) & ~1u) | tag, y = (__float_as_uint(b) & ~1u) | tag;
    const uint32_t z = (__float_as_uint(c) & ~1u) | tag, u = (__float_as_uint(d) & ~1u) | tag;
    asm volatile("{ .reg .b128 t, o; mov.b128 t, {%1, %2}; atom.relaxed.gpu.global.exch.b128 o, [%0], t; }" ::"l"(p),
                 "l"((unsigned long long)x | ((unsigned long long)y << 32)), "l"((unsigned long long)z | ((unsigned long long)u << 32)) : "memory");
}
__device__ __forceinline__ void st_mail1(float* p, uint32_t x) {
    asm volatile("st.relaxed.gpu.global.u32 [%0], %1;" ::"l"(p), "r"(x) : "memory");
}
__device__ __forceinline__ void st_async2(uint32_t dst, float a, float b, uint32_t bar) {
    asm volatile("st.async.weak.shared::cluster.mbarrier::complete_tx::bytes.v2.b32 [%0], {%1,%2}, [%3];"
                 ::"r"(dst), "r"(__float_as_uint(a)), "r"(__float_as_uint(b)), "r"(bar) : "memory");
}
__device__ __forceinline__ uint2 ld_poll2(const float* p) {
    uint2 v;
    asm volatile("ld.relaxed.gpu.global.v2.u32 {%0,%1}, [%2];" : "=r"(v.x), "=r"(v.y) : "l"(p) : "memory");
    return v;
}
__device__ __forceinline__ void lds4(float (&v)[4], uint32_t a) {
    asm volatile("ld.shared.v4.f32 {%0,%1,%2,%3}, [%4];" : "=f"(v[0]), "=f"(v[1]), "=f"(v[2]), "=f"(v[3]) : "r"(a) : "memory");
}
__device__ __forceinline__ uint4 lds4u(uint32_t a) {
    uint4 v; asm volatile("ld.shared.v4.u32 {%0,%1,%2,%3}, [%4];" : "=r"(v.x), "=r"(v.y), "=r"(v.z), "=r"(v.w) : "r"(a) : "memory"); return v;
}
__device__ __forceinline__ float lds1(uint32_t a) { float v; asm volatile("ld.shared.f32 %0, [%1];" : "=f"(v) : "r"(a) : "memory"); return v; }
__device__ __forceinline__ uint32_t lds1u(uint32_t a) { uint32_t v; asm volatile("ld.shared.u32 %0, [%1];" : "=r"(v) : "r"(a) : "memory"); return v; }
__device__ __forceinline__ void sts1(uint32_t a, float v) { asm volatile("st.shared.f32 [%0], %1;" ::"r"(a), "f"(v) : "memory"); }
__device__ __forceinline__ void sts2(uint32_t a, float v, float w) { asm volatile("st.shared.v2.f32 [%0], {%1,%2};" ::"r"(a), "f"(v), "f"(w) : "memory"); }
__device__ __forceinline__ void sts16(uint32_t a, float v) {
    asm volatile("{ .reg .b16 lo, hi; mov.b32 {lo, hi}, %1; st.shared.u16 [%0], lo; }" ::"r"(a), "r"(pack2(v, 0.f)) : "memory");
}
__device__ __forceinline__ void sts4u(uint32_t a, uint32_t x, uint32_t y, uint32_t z, uint32_t w) {
    asm volatile("st.shared.v4.u32 [%0], {%1,%2,%3,%4};" ::"r"(a), "r"(x), "r"(y), "r"(z), "r"(w) : "memory");
}

__device__ __forceinline__ uint32_t pin(uint32_t v) { return __shfl_sync(0xffffffffu, v, threadIdx.x & 31); }
template <class T>
__device__ __forceinline__ T* pin(T* p) {
    const unsigned long long v = (unsigned long long)p;
    return (T*)((unsigned long long)pin((uint32_t)v) | ((unsigned long long)pin((uint32_t)(v >> 32)) << 32));
}
__device__ __forceinline__ void sts1_if(bool c, uint32_t a, float v) {
    asm volatile("{ .reg .pred p; setp.ne.u32 p, %2, 0; @p st.shared.f32 [%0], %1; }" ::"r"(a), "f"(v), "r"((uint32_t)c) : "memory");
}
__device__ __forceinline__ uint32_t xor_or(uint32_t a, uint32_t b, uint32_t t) {
    uint32_t r; asm("lop3.b32 %0, %1, %2, %3, 0x7e;" : "=r"(r) : "r"(a), "r"(b), "r"(t)); return r;
}
template <int N>
__device__ __forceinline__ float tree_sum(float (&f)[N]) {
#pragma unroll
    for (int d = 1; d < N; d <<= 1)
#pragma unroll
        for (int i = 0; i + d < N; i += 2 * d) f[i] += f[i + d];
    return f[0];
}
__device__ __forceinline__ void spin_until(uint32_t due) {
    int it = 0;
    while ((int)(nsclock() - due) < 0 && ++it < SPIN_LIMIT) {}
}
__device__ __forceinline__ uint4 poll_packet(const float* src, uint32_t tmask) {
    uint4 v;
    int it = 0;
    do {
        v = ld_poll(src);
    } while (__any_sync(0xffffffffu, (xor_or(v.x, v.y, tmask) | xor_or(v.z, v.w, tmask)) & 1u) && ++it < POLL_LIMIT);
    return v;
}

__device__ __forceinline__ float rcp_(float v) { float r; asm("rcp.approx.ftz.f32 %0, %1;" : "=f"(r) : "f"(v)); return r; }
__device__ __forceinline__ float sqrt_(float v) { float r; asm("sqrt.approx.ftz.f32 %0, %1;" : "=f"(r) : "f"(v)); return r; }
__device__ __forceinline__ float ln_rden(float var) { return rcp_(bfr(sqrt_(bfr(bfr(var) + 1e-5f)))); }

template <int NSLOT>
__global__ void __launch_bounds__(kThreads, NSLOT <= 6 ? 2 : 1)
fused_decode(const __grid_constant__ CUtensorMap tm_wq, const __grid_constant__ CUtensorMap tm_k,
             const __grid_constant__ CUtensorMap tm_v, const __grid_constant__ CUtensorMap tm_wo,
             const __grid_constant__ CUtensorMap tm_g, const __grid_constant__ CUtensorMap tm_u,
             const __grid_constant__ CUtensorMap tm_d, const Params p) {
    extern __shared__ uint8_t smem_raw[];
    const uint32_t sb = (s2u(smem_raw) + 1023u) & ~1023u;
    const uint32_t mb_ = sb + NSLOT * SLOT;
    const int t = threadIdx.x, w = t >> 5, lane = t & 31, grp = lane >> 2, hq = lane & 3;
    const int cta = blockIdx.x, r = cta & 7, cl = cta >> 3;
    const uint32_t bar0 = mb_ + OFF_BAR;
    const uint32_t ns0 = nsclock();
#define FULL(s) (bar0 + 8 * (s))
#define EMPTY(s) (bar0 + 128 + 8 * (s))
#define XBAR(i) (bar0 + 256 + 8 * (i))
#define MFULL(i) ((i) < 6 ? FULL(i) : EMPTY((i) - 6))
    if (w == 8) {
        if (lane == 0) {
            mbar_init(FULL(0), 1);
            asm volatile("fence.mbarrier_init.release.cluster;" ::: "memory");
            if (cta < kAttn) { mbar_expect(FULL(0), SLOT); tma3d(sb, &tm_wq, 64 * cta, 0, 0, FULL(0)); }
#pragma unroll
            for (int s = 1; s < NSLOT; s++) mbar_init(FULL(s), 1);
#pragma unroll
            for (int s = 0; s < NSLOT; s++) mbar_init(EMPTY(s), cta < kAttn ? 8 : 1);
            asm volatile("fence.mbarrier_init.release.cluster;" ::: "memory");
        }
        __syncwarp();
        if (cta < kAttn) { if (lane >= 1 && lane < NSLOT) mbar_expect(FULL(lane), SLOT); }
        else if (lane < 8) mbar_expect(MFULL(lane), SLOT / 2);
    }
    if (t == 64) {
#pragma unroll
        for (int i = 0; i < 5; i++) mbar_init(XBAR(i), 1);
        asm volatile("fence.mbarrier_init.release.cluster;" ::: "memory");
        mbar_expect(XBAR(0), 1024);
        mbar_expect(XBAR(1), 128);
        mbar_expect(XBAR(2), cta < kAttn ? 2048 : 128);
        mbar_expect(XBAR(3), 2048);
        mbar_expect(XBAR(4), 1024);
    }
    __syncwarp();
    cluster_arrive();

    if (cta < kAttn) {
        const int g = cl, b = r >> 2, j = r & 3;
        if (w == 9) {
            bar_arrive(0, kThreads);
        } else if (w == 8) {
            bar_arrive(0, kThreads);
            if (lane == 0) {
                const int kvrow = (b * 8 + g) * 8192 + 6144 + 512 * j;
                uint32_t dst = sb + SLOT, fb = FULL(1), fend = FULL(NSLOT), ph = 1;
                asm volatile("" : "+r"(dst), "+r"(fb), "+r"(fend));
                int i = 1;
                const uint32_t pace = p.pace;
                uint32_t due = ns0 - p.lead + ((cta * 37) & 63) * p.stag;
                auto run = [&](const CUtensorMap* m, int c0, int c1, int step, int n, uint32_t bytes) {
#pragma unroll 1
                    for (; n > 0; n--, i++, c1 += step) {
                        if (i >= NSLOT) { mbar_wait(fb + 128, ph); mbar_expect(fb, bytes); }
                        due += pace;
                        spin_until(due);
                        tma3d(dst, m, c0, c1, 0, fb);
                        dst += SLOT; fb += 8;
                        if (fb == fend) { fb -= 8 * NSLOT; dst -= SLOT * NSLOT; ph ^= 1; }
                    }
                };
                run(&tm_wq, 64 * cta, 128, 128, 3, SLOT);
                run(&tm_k, 0, kvrow, 64, 8, SLOT);
                run(&tm_v, 0, kvrow, 64, 8, SLOT);
                run(&tm_wo, 64 * r, 512 * g, 128, 4, SLOT);
                due += p.dn_gap;
                run(&tm_d, 64 * g, 224 * r, 112, 2, 14336);
                PROF(8);
                PROF_DUMP();
            }
            __syncwarp();
            cluster_wait();
        } else {
            if (w < 2) {
                const uint4* xp = reinterpret_cast<const uint4*>(p.x + w * 512 + lane * 16);
                const uint4 xa = __ldg(xp), xb = __ldg(xp + 1);
                const uint32_t u[8] = {xa.x, xa.y, xa.z, xa.w, xb.x, xb.y, xb.z, xb.w};
                float v[16], f[16];
#pragma unroll
                for (int i = 0; i < 8; i++) { v[2 * i] = bflo(u[i]); v[2 * i + 1] = bfhi(u[i]); }
#pragma unroll
                for (int i = 0; i < 16; i++) f[i] = v[i];
                float sm = tree_sum(f);
#pragma unroll
                for (int o = 16; o; o >>= 1) sm += __shfl_xor_sync(0xffffffffu, sm, o);
                const float mean = sm * (1.f / 512.f);
#pragma unroll
                for (int i = 0; i < 16; i++) { const float d = v[i] - mean; f[i] = d * d; }
                float sq = tree_sum(f);
#pragma unroll
                for (int o = 16; o; o >>= 1) sq += __shfl_xor_sync(0xffffffffu, sq, o);
                const float mb = bfr(mean), rden = ln_rden(sq * (1.f / 512.f));
                uint32_t o[8];
#pragma unroll
                for (int i = 0; i < 8; i++) {
                    const uint32_t c = pack2(v[2 * i] - mb, v[2 * i + 1] - mb);
                    o[i] = pack2(bflo(c) * rden, bfhi(c) * rden);
                }
                const uint32_t d = mb_ + A_XN + w * 1040 + lane * 32;
                sts4u(d, o[0], o[1], o[2], o[3]);
                sts4u(d + 16, o[4], o[5], o[6], o[7]);
            }
            unsigned ep;
            asm volatile("ld.relaxed.gpu.global.u32 %0, [%1];" : "=r"(ep) : "l"(p.epoch) : "memory");
            uint2 xr;
            asm volatile("ld.global.nc.v2.u32 {%0,%1}, [%2];" : "=r"(xr.x), "=r"(xr.y) : "l"(p.x + (hq >> 1) * 512 + 8 * cta + (hq & 1) * 4));
            const int mt = w & 3, hp = w >> 2, h0 = 2 * (hq & 1);
            const int mi = lane >> 3, rr = (lane & 7) + (mi >> 1) * 8;
            const uint32_t act_off = (lane & 7) * 1040 + hp * 128 + mi * 16;
            const uint32_t wt_off = sb + (64 * hp + rr) * 128 + (((2 * mt + (mi & 1)) ^ (rr & 7)) << 4);
            uint32_t gp_st = mb_ + A_GP + hp * 512 + (16 * mt + grp) * 4;
            constexpr float L2E = 1.4426950408889634f;
            bar_sync(0, kThreads);
            PROF(0);
            {
                float acc[2][4] = {};
#pragma unroll 1
                for (int i = 0; i < 4; i++) {
                    uint32_t bf[2][4];
                    ldsm4(bf[0], mb_ + A_XN + act_off + i * 256);
                    ldsm4(bf[1], mb_ + A_XN + act_off + i * 256 + 64);
                    mbar_wait(FULL(i), 0);
                    if (i == 0) PROF(2);
#pragma unroll
                    for (int k = 0; k < 4; k++) {
                        uint32_t a[4];
                        ldsm4t(a, wt_off + i * SLOT + k * 2048);
                        mma(acc[k & 1], a[0], a[1], a[2], a[3], bf[k >> 1][(k & 1) * 2], bf[k >> 1][(k & 1) * 2 + 1]);
                    }
                    __syncwarp();
                    if (lane == 0) mbar_arrive(EMPTY(i));
                }
                if (hq == 0) {
                    sts1(gp_st, acc[0][0] + acc[1][0]); sts1(gp_st + 256, acc[0][1] + acc[1][1]);
                    sts1(gp_st + 32, acc[0][2] + acc[1][2]); sts1(gp_st + 256 + 32, acc[0][3] + acc[1][3]);
                }
                cluster_wait();
                bar_sync(1, 256);
                if (w < 2) {
                    const int tg = t >> 3, pc = t & 7;
                    const uint32_t src = mb_ + A_GP + (tg >> 2) * 256 + pc * 32;
                    float u0[4], u1[4], v0[4], v1[4];
                    lds4(u0, src); lds4(u1, src + 16); lds4(v0, src + 512); lds4(v1, src + 512 + 16);
                    st_async4(mapa(mb_ + A_Q + (r >> 1) * 272 + (r & 1) * 128 + pc * 16, tg), pack2(u0[0] + v0[0], u0[1] + v0[1]),
                              pack2(u0[2] + v0[2], u0[3] + v0[3]), pack2(u1[0] + v1[0], u1[1] + v1[1]), pack2(u1[2] + v1[2], u1[3] + v1[3]),
                              mapa(XBAR(0), tg));
                }
            }
            if (w == 2) st_mail4(p.attn_part + g * 1024 + r * 128 + lane * 4, ep & 1);
            PROF(1);
            int s = 4, ph = 0;
            float sc[4][4] = {};
            {
                mbar_wait(XBAR(0), 0);
                uint32_t qf[4][4];
#pragma unroll
                for (int i = 0; i < 4; i++) ldsm4(qf[i], mb_ + A_Q + (lane & 7) * 272 + i * 64 + (lane >> 3) * 16);
                const int row = 16 * mt + (lane & 7) + ((lane >> 3) & 1) * 8;
                const uint32_t x0a = row * 128 + ((((lane >> 4) ^ (row & 7))) << 4);
#pragma unroll 1
                for (int c = 0; c < 8; c++) {
                    if ((c & 1) == hp) {
                        mbar_wait(FULL(s), ph);
                        float s0[4] = {}, s1[4] = {};
                        const uint32_t kb = sb + s * SLOT;
#pragma unroll
                        for (int ks = 0; ks < 8; ks++) {
                            uint32_t a[4];
                            ldsm4(a, kb + (ks >> 2) * 8192 + (x0a ^ ((ks & 3) << 5)));
                            if (ks & 1) mma(s1, a[0], a[1], a[2], a[3], qf[ks >> 1][2], qf[ks >> 1][3]);
                            else mma(s0, a[0], a[1], a[2], a[3], qf[ks >> 1][0], qf[ks >> 1][1]);
                        }
#pragma unroll
                        for (int k = 0; k < 3; k++)
#pragma unroll
                            for (int e = 0; e < 4; e++) sc[k][e] = sc[k + 1][e];
                        const uint32_t r1 = pack2(s0[0] + s1[0], s0[1] + s1[1]), r3 = pack2(s0[2] + s1[2], s0[3] + s1[3]);
                        const uint32_t r2 = pack2(bflo(r1) * 0.08838834764831845f, bfhi(r1) * 0.08838834764831845f);
                        const uint32_t r4 = pack2(bflo(r3) * 0.08838834764831845f, bfhi(r3) * 0.08838834764831845f);
                        sc[3][0] = bflo(r2); sc[3][1] = bfhi(r2); sc[3][2] = bflo(r4); sc[3][3] = bfhi(r4);
                        __syncwarp();
                        if (lane < 2) mbar_arrive(EMPTY(s));
                    }
                    if (++s == NSLOT) { s = 0; ph ^= 1; }
                }
            }
            PROF(3);
            {
                float m0 = fmaxf(fmaxf(fmaxf(sc[0][0], sc[1][0]), fmaxf(sc[2][0], sc[3][0])), fmaxf(fmaxf(sc[0][2], sc[1][2]), fmaxf(sc[2][2], sc[3][2])));
                float m1 = fmaxf(fmaxf(fmaxf(sc[0][1], sc[1][1]), fmaxf(sc[2][1], sc[3][1])), fmaxf(fmaxf(sc[0][3], sc[1][3]), fmaxf(sc[2][3], sc[3][3])));
#pragma unroll
                for (int o = 4; o <= 16; o <<= 1) {
                    m0 = fmaxf(m0, __shfl_xor_sync(0xffffffffu, m0, o));
                    m1 = fmaxf(m1, __shfl_xor_sync(0xffffffffu, m1, o));
                }
                if (lane < 2) { sts1(mb_ + A_WM + h0 * 32 + w * 4, m0); sts1(mb_ + A_WM + h0 * 32 + 32 + w * 4, m1); }
                bar_sync(1, 256);
                float a0[4], a1[4], b0[4], b1[4];
                lds4(a0, mb_ + A_WM + h0 * 32); lds4(a1, mb_ + A_WM + h0 * 32 + 16);
                lds4(b0, mb_ + A_WM + h0 * 32 + 32); lds4(b1, mb_ + A_WM + h0 * 32 + 48);
                m0 = fmaxf(fmaxf(fmaxf(a0[0], a0[1]), fmaxf(a0[2], a0[3])), fmaxf(fmaxf(a1[0], a1[1]), fmaxf(a1[2], a1[3])));
                m1 = fmaxf(fmaxf(fmaxf(b0[0], b0[1]), fmaxf(b0[2], b0[3])), fmaxf(fmaxf(b1[0], b1[1]), fmaxf(b1[2], b1[3])));
                const uint32_t pa = mb_ + A_P + h0 * 1040 + (64 * hp + 16 * mt + grp) * 2;
                float l0 = 0.f, l1 = 0.f;
#pragma unroll
                for (int i = 0; i < 4; i++) {
                    const float e0 = ex2((sc[i][0] - m0) * L2E), e1 = ex2((sc[i][1] - m1) * L2E);
                    const float e2 = ex2((sc[i][2] - m0) * L2E), e3 = ex2((sc[i][3] - m1) * L2E);
                    if (hq < 2) {
                        sts16(pa + i * 256, e0);
                        sts16(pa + i * 256 + 1040, e1);
                        sts16(pa + i * 256 + 16, e2);
                        sts16(pa + i * 256 + 1040 + 16, e3);
                    }
                    l0 += e0 + e2; l1 += e1 + e3;
                }
#pragma unroll
                for (int o = 4; o <= 16; o <<= 1) {
                    l0 += __shfl_xor_sync(0xffffffffu, l0, o);
                    l1 += __shfl_xor_sync(0xffffffffu, l1, o);
                }
                if (lane < 2) { sts1(mb_ + A_WS + h0 * 32 + w * 4, l0); sts1(mb_ + A_WS + h0 * 32 + 32 + w * 4, l1); }
                bar_sync(1, 256);
                if (w == 7) {
                    lds4(a0, mb_ + A_WS + h0 * 32); lds4(a1, mb_ + A_WS + h0 * 32 + 16);
                    lds4(b0, mb_ + A_WS + h0 * 32 + 32); lds4(b1, mb_ + A_WS + h0 * 32 + 48);
                    l0 = ((a0[0] + a0[1]) + (a0[2] + a0[3])) + ((a1[0] + a1[1]) + (a1[2] + a1[3]));
                    l1 = ((b0[0] + b0[1]) + (b0[2] + b0[3])) + ((b1[0] + b1[1]) + (b1[2] + b1[3]));
                    if (lane < 8) {
                        const uint32_t tgt = 4 * b + (lane >> 1);
                        st_async4(mapa(mb_ + A_ST + j * 32 + (lane & 1) * 16, tgt), __float_as_uint(m0), __float_as_uint(l0),
                                  __float_as_uint(m1), __float_as_uint(l1), mapa(XBAR(1), tgt));
                    }
                }
            }
            PROF(4);
            {
                float o0[4] = {}, o1[4] = {};
                const int ch = 2 * w + (mi & 1);
                const uint32_t voff = sb + (ch >> 3) * 8192 + rr * 128 + (((ch & 7) ^ (rr & 7)) << 4);
                const uint32_t poff = mb_ + A_P + (lane & 7) * 1040 + (lane >> 3) * 16;
#pragma unroll 1
                for (int c = 0; c < 8; c++) {
                    uint32_t pf[2][4];
                    ldsm4(pf[0], poff + c * 128);
                    ldsm4(pf[1], poff + c * 128 + 64);
                    mbar_wait(FULL(s), ph);
#pragma unroll
                    for (int ks = 0; ks < 4; ks++) {
                        uint32_t a[4];
                        ldsm4t(a, voff + s * SLOT + ks * 2048);
                        if (ks & 1) mma(o1, a[0], a[1], a[2], a[3], pf[ks >> 1][2], pf[ks >> 1][3]);
                        else mma(o0, a[0], a[1], a[2], a[3], pf[ks >> 1][0], pf[ks >> 1][1]);
                    }
                    __syncwarp();
                    if (lane == 0) mbar_arrive(EMPTY(s));
                    if (++s == NSLOT) { s = 0; ph ^= 1; }
                }
                PROF(5);
                if (hq < 2) {
                    const uint32_t d = mb_ + A_OP + h0 * 544 + (16 * w + grp) * 4;
                    sts1(d, o0[0] + o1[0]);
                    sts1(d + 544, o0[1] + o1[1]);
                    sts1(d + 32, o0[2] + o1[2]);
                    sts1(d + 544 + 32, o0[3] + o1[3]);
                }
            }
            if (w < 4) {
                mbar_wait(XBAR(1), 0);
                float f[4];
                {
                    float mm[4], ll[4];
#pragma unroll
                    for (int i = 0; i < 4; i++) { mm[i] = lds1(mb_ + A_ST + i * 32 + j * 8); ll[i] = lds1(mb_ + A_ST + i * 32 + j * 8 + 4); }
                    const float M = fmaxf(fmaxf(mm[0], mm[1]), fmaxf(mm[2], mm[3]));
#pragma unroll
                    for (int i = 0; i < 4; i++) f[i] = ex2((mm[i] - M) * L2E);
                    const float inv = rcp_((ll[0] * f[0] + ll[1] * f[1]) + (ll[2] * f[2] + ll[3] * f[3]));
#pragma unroll
                    for (int i = 0; i < 4; i++) f[i] *= inv;
                }
                bar_sync(1, 256);
                const uint4 v = lds4u(mb_ + A_OP + w * 544 + lane * 16);
                const uint32_t tgt = 4 * b + w;
                st_async4(mapa(mb_ + A_RS + j * 512 + lane * 16, tgt), v.x, v.y, v.z, v.w, mapa(XBAR(2), tgt));
                const int tg2 = t >> 4, pc = t & 15;
                const uint32_t da = mapa(mb_ + A_O + b * 1040 + j * 256 + pc * 16, tg2), db = mapa(XBAR(3), tg2);
                mbar_wait(XBAR(2), 0);
                float u[4][8];
#pragma unroll
                for (int i = 0; i < 4; i++) {
                    lds4(*reinterpret_cast<float(*)[4]>(&u[i][0]), mb_ + A_RS + i * 512 + pc * 32);
                    lds4(*reinterpret_cast<float(*)[4]>(&u[i][4]), mb_ + A_RS + i * 512 + pc * 32 + 16);
                }
                float o8[8];
#pragma unroll
                for (int k = 0; k < 8; k++) o8[k] = (u[0][k] * f[0] + u[1][k] * f[1]) + (u[2][k] * f[2] + u[3][k] * f[3]);
                st_async4(da, pack2(o8[0], o8[1]), pack2(o8[2], o8[3]), pack2(o8[4], o8[5]), pack2(o8[6], o8[7]), db);
            } else {
                bar_arrive(1, 256);
            }
            const uint32_t tag = pin((ep + 1) & 1);
            {
                float* pub = pin(p.attn_part + g * 1024 + r * 128 + lane * 4);
                const uint32_t oa = pin(mb_ + A_O + act_off), gp_ld = pin(mb_ + A_GP + lane * 16);
                gp_st = pin(gp_st);
                uint32_t wf[3][4][4];
#pragma unroll
                for (int c = 0; c < 3; c++) {
                    mbar_wait(FULL(s), ph);
#pragma unroll
                    for (int k = 0; k < 4; k++) ldsm4t(wf[c][k], wt_off + s * SLOT + k * 2048);
                    if (++s == NSLOT) { s = 0; ph ^= 1; }
                }
                const uint32_t wl = pin(wt_off + s * SLOT), fl = pin(FULL(s));
                mbar_wait(XBAR(3), 0);
                PROF(6);
                uint32_t bf[4][2][4];
#pragma unroll
                for (int c = 0; c < 4; c++) { ldsm4(bf[c][0], oa + c * 256); ldsm4(bf[c][1], oa + c * 256 + 64); }
                float acc[4][4] = {};
#pragma unroll
                for (int c = 0; c < 3; c++)
#pragma unroll
                    for (int k = 0; k < 4; k++)
                        mma(acc[k], wf[c][k][0], wf[c][k][1], wf[c][k][2], wf[c][k][3], bf[c][k >> 1][(k & 1) * 2], bf[c][k >> 1][(k & 1) * 2 + 1]);
                mbar_wait(fl, ph);
                PROF(9);
#pragma unroll
                for (int k = 0; k < 4; k++) {
                    uint32_t a[4];
                    ldsm4t(a, wl + k * 2048);
                    mma(acc[k], a[0], a[1], a[2], a[3], bf[3][k >> 1][(k & 1) * 2], bf[3][k >> 1][(k & 1) * 2 + 1]);
                }
                if (hq == 0) {
                    sts1(gp_st, (acc[0][0] + acc[1][0]) + (acc[2][0] + acc[3][0]));
                    sts1(gp_st + 256, (acc[0][1] + acc[1][1]) + (acc[2][1] + acc[3][1]));
                    sts1(gp_st + 32, (acc[0][2] + acc[1][2]) + (acc[2][2] + acc[3][2]));
                    sts1(gp_st + 256 + 32, (acc[0][3] + acc[1][3]) + (acc[2][3] + acc[3][3]));
                }
                if (w == 2) {
                    bar_sync(1, 256);
                    float u[4], v[4];
                    lds4(u, gp_ld); lds4(v, gp_ld + 512);
                    exch_tag4(pub, u[0] + v[0], u[1] + v[1], u[2] + v[2], u[3] + v[3], tag);
                    PROFL(12);
                } else {
                    bar_arrive(1, 256);
                }
                PROF(7);
            }
            const uint32_t tmask = 0u - tag;
            {
                const float* src = pin(w == 0 ? p.attn_part + grp * 1024 + cl * 128 + (hq >> 1) * 64 + r * 8 + (hq & 1) * 4
                                              : p.hh_mail + ((7 * r + w - 1) * 2 + (lane >> 4)) * kHhStride + (lane & 15) * 2);
                __nv_bfloat16* outp = pin(p.out + (lane & 1) * 512 + 8 * cta + ((lane >> 1) & 7));
                const uint32_t hs = pin(mb_ + A_HH + (lane >> 4) * 464 + (w - 1) * 64 + (lane & 15) * 4);
                const uint32_t hl = pin(mb_ + A_HH + (lane & 7) * 464 + hp * 224 + mi * 16);
                const uint32_t fl = pin(mb_ + A_FIN + (lane >> 4) * 512 + (lane & 15) * 4);
                const uint32_t fd = mb_ + A_FIN + ((2 * r + hp) * 8 + grp) * 8;
                const uint32_t da0 = pin(mapa(fd, 2 * mt)), da1 = pin(mapa(fd, 2 * mt + 1));
                const uint32_t db0 = pin(mapa(XBAR(4), 2 * mt)), db1 = pin(mapa(XBAR(4), 2 * mt + 1));
                if (++s == NSLOT) { s = 0; ph ^= 1; }
                s += hp;
                const uint32_t fdn = pin(FULL(s)), dn = pin(wt_off - hp * 8192 + s * SLOT);
                uint32_t df[7][4];
                auto stage_dn = [&]() {
                    mbar_wait(fdn, ph);
#pragma unroll
                    for (int k = 0; k < 7; k++) ldsm4t(df[k], dn + k * 2048);
                };
                bool early = false;
                if (w == 0) {
                    const uint4 v = poll_packet(src, tmask);
                    float d4[4] = {__uint_as_float(v.x), __uint_as_float(v.y), __uint_as_float(v.z), __uint_as_float(v.w)};
#pragma unroll
                    for (int o = 4; o <= 16; o <<= 1) {
#pragma unroll
                        for (int i = 0; i < 4; i++) d4[i] += __shfl_xor_sync(0xffffffffu, d4[i], o);
                    }
                    if (lane < 4) {
                        const uint32_t d = mb_ + A_HS + (hq & 1) * 32 + (hq >> 1) * 4;
                        sts1(d, bfr(bflo(xr.x) + bfr(d4[0])));
                        sts1(d + 8, bfr(bfhi(xr.x) + bfr(d4[1])));
                        sts1(d + 16, bfr(bflo(xr.y) + bfr(d4[2])));
                        sts1(d + 24, bfr(bfhi(xr.y) + bfr(d4[3])));
                    }
                    PROF(10);
                } else {
                    uint2 v;
                    int it = 0;
                    do {
                        if (!early && __all_sync(0xffffffffu, mbar_test(fdn, ph))) { early = true; stage_dn(); }
                        v = ld_poll2(src);
                    } while (__any_sync(0xffffffffu, xor_or(v.x, v.y, tmask) & 1u) && ++it < POLL_LIMIT);
                    asm volatile("st.shared.u32 [%0], %1;" ::"r"(hs), "r"(__byte_perm(v.x, v.y, 0x7632)) : "memory");
                }
                if (!early) stage_dn();
                bar_sync(3, 256);
                uint32_t bf[4][4];
#pragma unroll
                for (int k = 0; k < 4; k++) ldsm4(bf[k], hl + k * 64);
                float acc[2][4] = {};
#pragma unroll
                for (int k = 0; k < 7; k++) mma(acc[k & 1], df[k][0], df[k][1], df[k][2], df[k][3], bf[k >> 1][(k & 1) * 2], bf[k >> 1][(k & 1) * 2 + 1]);
                if (hq == 0) {
                    st_async2(da0, acc[0][0] + acc[1][0], acc[0][1] + acc[1][1], db0);
                    st_async2(da1, acc[0][2] + acc[1][2], acc[0][3] + acc[1][3], db1);
                }
                if (w == 0) {
                    const float hv = lds1(mb_ + A_HS + (lane & 15) * 4);
                    mbar_wait(XBAR(4), 0);
                    float f[8];
#pragma unroll
                    for (int i = 0; i < 8; i++) f[i] = lds1(fl + i * 64);
                    float d = tree_sum(f);
                    d += __shfl_xor_sync(0xffffffffu, d, 16);
                    if (lane < 16) *reinterpret_cast<unsigned short*>(outp) = (unsigned short)pack2(hv + bfr(d), 0.f);
                    if (cta == 0 && lane == 0) *p.epoch = ep + 1;
                    PROF(11);
                }
            }
            PROF_DUMP();
        }
    } else {
        const int m = cta - kAttn;
        unsigned ep;
        asm volatile("ld.relaxed.gpu.global.u32 %0, [%1];" : "=r"(ep) : "l"(p.epoch) : "memory");
        if (w >= 8) {
            uint2 xv;
            asm volatile("ld.global.nc.v2.u32 {%0,%1}, [%2];" : "=r"(xv.x), "=r"(xv.y) : "l"(p.x + (lane >> 4) * 512 + 64 * r + (lane & 15) * 4));
            bar_sync(0, kThreads);
            cluster_wait();
            const uint32_t dst = mb_ + M_H + (lane >> 4) * 1040 + 128 * r + ((lane & 15) >> 1) * 16;
            const uint32_t sl = pin(mb_ + M_SP + (lane >> 4) * 64), gl = pin(mb_ + M_G3 + lane * 16);
            uint32_t da[4], db[4];
#pragma unroll
            for (int i = 0; i < 4; i++) {
                da[i] = pin(w == 8 ? mapa(dst, 2 * i + (lane & 1)) : mapa(sl + r * 8, lane & 7));
                db[i] = pin(w == 8 ? mapa(XBAR(3), 2 * i + (lane & 1)) : mapa(XBAR(2), lane & 7));
            }
            float xf[4] = {bflo(xv.x), bfhi(xv.x), bflo(xv.y), bfhi(xv.y)};
#pragma unroll
            for (int k = 0; k < 4; k++) xf[k] = __uint_as_float(pin(__float_as_uint(xf[k])));
            if (w == 9 && lane == 0) {
#pragma unroll 1
                for (int i = 0; i < 8; i++) {
                    spin_until(ns0 + p.mlp_t0 + i * p.mlp_dt + ((m * 37) & 63) * p.mlp_stag);
                    tma2d(sb + (i & 1) * 32768 + (i >> 1) * 8192, (i & 1) ? &tm_u : &tm_g, 32 * m, 128 * (i >> 1), MFULL(i));
                }
            }
            __syncwarp();
            bar_sync(3, kThreads);
            float u[8][4], a4[4];
#pragma unroll
            for (int i = 0; i < 8; i++) lds4(u[i], gl + i * 512);
#pragma unroll
            for (int k = 0; k < 4; k++) a4[k] = xf[k] + bfr(((u[0][k] + u[1][k]) + (u[2][k] + u[3][k])) + ((u[4][k] + u[5][k]) + (u[6][k] + u[7][k])));
            const uint32_t hw0 = pack2(a4[0], a4[1]), hw1 = pack2(a4[2], a4[3]);
            if (w == 8) {
                const uint32_t ow0 = __shfl_xor_sync(0xffffffffu, hw0, 1), ow1 = __shfl_xor_sync(0xffffffffu, hw1, 1);
                const bool odd = lane & 1;
                const uint32_t e0 = odd ? ow0 : hw0, e1 = odd ? ow1 : hw1, e2 = odd ? hw0 : ow0, e3 = odd ? hw1 : ow1;
#pragma unroll
                for (int i = 0; i < 4; i++) st_async4(da[i], e0, e1, e2, e3, db[i]);
                PROF(9);
                PROF_DUMP();
            } else {
                const float h0 = bflo(hw0), h1 = bfhi(hw0), h2 = bflo(hw1), h3 = bfhi(hw1);
                float s1 = (h0 + h1) + (h2 + h3), s2 = fmaf(h0, h0, h1 * h1) + fmaf(h2, h2, h3 * h3);
#pragma unroll
                for (int o = 8; o; o >>= 1) { s1 += __shfl_xor_sync(0xffffffffu, s1, o); s2 += __shfl_xor_sync(0xffffffffu, s2, o); }
                if (!(lane & 8))
                    asm volatile("st.async.weak.shared::cluster.mbarrier::complete_tx::bytes.v2.b32 [%0], {%1,%2}, [%3];"
                                 ::"r"(da[0]), "r"(__float_as_uint(s1)), "r"(__float_as_uint(s2)), "r"(db[0]) : "memory");
                mbar_wait(XBAR(2), 0);
                float u0[4], u1[4], u2[4], u3[4];
                lds4(u0, sl); lds4(u1, sl + 16); lds4(u2, sl + 32); lds4(u3, sl + 48);
                const float mean = (((u0[0] + u0[2]) + (u1[0] + u1[2])) + ((u2[0] + u2[2]) + (u3[0] + u3[2]))) * (1.f / 512.f);
                const float msq = (((u0[1] + u0[3]) + (u1[1] + u1[3])) + ((u2[1] + u2[3]) + (u3[1] + u3[3]))) * (1.f / 512.f);
                const float var = fmaxf(fmaf(-mean, mean, msq), 0.f);
                sts2(mb_ + M_ST + (lane >> 4) * 8, bfr(mean), ln_rden(var));
                PROFL(10);
                bar_arrive(2, 288);
            }
        } else {
            if (t < 32) asm volatile("st.shared.u32 [%0], %1;" ::"r"(mb_ + M_CS + (t & 31) * 4), "r"(0x3f803f80u) : "memory");
            bar_sync(0, kThreads);
            cluster_wait();
            const int mi = lane >> 3, rr = (lane & 7) + (mi >> 1) * 8;
            const int bb = (w >> 1) & 1, mat = lane >> 4, col = (w & 1) * 16 + (lane & 15);
            float* dout = pin(p.hh_mail + (m * 2 + bb) * kHhStride + col);
            const uint32_t tag = pin((ep + 1) & 1);
            const uint32_t ha = pin(grp < 6 ? mb_ + M_H + (grp & 1) * 1040 + w * 128 + hq * 4 : mb_ + M_CS + hq * 4);
            const bool h3 = hq == 3;
            const uint32_t ps0 = pin(h3 ? mb_ + M_CSP + w * 256 + grp * 4 : mb_ + M_PART + w * 768 + ((hq >> 1) * 48 + (hq & 1) * 16 + grp) * 4);
            const uint32_t ps1 = pin(ps0 + (h3 ? 32 : 384)), ps2 = pin(ps0 + (h3 ? 64 : 32)), ps3 = pin(ps0 + (h3 ? 96 : 416));
            const uint32_t pd2 = pin(h3 ? 128 : 256), hq1 = pin(hq & 1), hq2 = pin(hq & 2), second = pin(hq == 0 || h3);
            const uint32_t pld = pin(mb_ + M_PART + bb * 384 + (mat * 48 + col) * 4), cld = pin(mb_ + M_CSP + (mat * 32 + col) * 4);
            const uint32_t sld = pin(mb_ + M_ST + bb * 8), xb = pin(XBAR(3));
            const uint32_t g3 = pin(mb_ + M_G3 + w * 512 + lane * 16);
            uint32_t wf[4][4][4];
            const uint32_t fa = MFULL(w & 6), fb = fa + 8;
            bool ready;
            {
                int it = 0;
                do { ready = mbar_test(fa, 0) && mbar_test(fb, 0); } while (!ready && nsclock() - ns0 < (uint32_t)p.poll_t0 && ++it < SPIN_LIMIT);
            }
            ready = __all_sync(0xffffffffu, ready);
            auto stage_gu = [&]() {
                mbar_wait(fa, 0);
                mbar_wait(fb, 0);
#pragma unroll
                for (int tl = 0; tl < 4; tl++)
#pragma unroll
                    for (int ks = 0; ks < 4; ks++) {
                        const int row = 64 * w + 16 * ks + rr;
                        const int ch = 2 * (tl & 1) + (mi & 1);
                        ldsm4t(wf[tl][ks], sb + (tl >> 1) * 32768 + row * 64 + ((ch ^ ((row >> 1) & 3)) << 4));
                    }
                PROF(0);
            };
            if (ready) stage_gu();
            {
                spin_until(ns0 + p.poll_t0);
                const uint4 v = poll_packet(p.attn_part + w * 1024 + r * 128 + lane * 4, 0u - tag);
                sts4u(g3, v.x, v.y, v.z, v.w);
                bar_arrive(3, kThreads);
            }
            if (!ready) stage_gu();
            PROF(4);
            {
                {
                    mbar_wait(xb, 0);
                    PROF(1);
                    uint32_t hf[8];
#pragma unroll
                    for (int k = 0; k < 8; k++) hf[k] = lds1u(ha + k * 16);
                    float c[4][4] = {};
#pragma unroll
                    for (int ks = 0; ks < 4; ks++)
#pragma unroll
                        for (int tl = 0; tl < 4; tl++)
                            mma(c[tl], wf[tl][ks][0], wf[tl][ks][1], wf[tl][ks][2], wf[tl][ks][3], hf[2 * ks], hf[2 * ks + 1]);
                    const float v0 = hq2 ? (hq1 ? c[0][0] : c[2][0]) : (hq1 ? c[1][0] : c[0][0]);
                    const float v1 = hq2 ? (hq1 ? c[0][2] : c[2][1]) : (hq1 ? c[1][1] : c[0][1]);
                    const float v2 = hq2 ? (hq1 ? c[1][0] : c[2][2]) : (hq1 ? c[1][2] : c[0][2]);
                    const float v3 = hq2 ? (hq1 ? c[1][2] : c[2][3]) : (hq1 ? c[1][3] : c[0][3]);
                    sts1(ps0, v0); sts1(ps1, v1); sts1(ps2, v2); sts1(ps3, v3);
                    sts1_if(second, ps0 + pd2, hq2 ? c[2][0] : c[3][0]);
                    sts1_if(second, ps1 + pd2, hq2 ? c[2][2] : c[3][1]);
                    sts1_if(second, ps2 + pd2, hq2 ? c[3][0] : c[3][2]);
                    sts1_if(second, ps3 + pd2, hq2 ? c[3][2] : c[3][3]);
                    if (w < 4) {
                        bar_sync(2, 288);
                        float f[8], cf[8];
#pragma unroll
                        for (int i = 0; i < 8; i++) f[i] = lds1(pld + i * 768);
#pragma unroll
                        for (int i = 0; i < 8; i++) cf[i] = lds1(cld + i * 256);
                        const float mean = lds1(sld), rs = lds1(sld + 4);
                        const float g = bfr(fmaf(-mean, tree_sum(cf), tree_sum(f)) * rs);
                        const float u = __shfl_xor_sync(0xffffffffu, g, 16);
                        const float e = ex2(g * fmaf(g * g, -0.10294324f, -2.3022082f));
                        const float ge = bfr(g * rcp_(1.f + e));
                        if (lane < 16) st_mail1(dout, pack2(0.f, ge * u) | tag);
                        PROF(2);
                    } else {
                        bar_arrive(2, 288);
                    }
                }
            }
            PROF(3);
            PROF_DUMP();
        }
    }
}

typedef CUresult (*EncodeFn)(CUtensorMap*, CUtensorMapDataType, cuuint32_t, void*, const cuuint64_t*, const cuuint64_t*,
                             const cuuint32_t*, const cuuint32_t*, CUtensorMapInterleave, CUtensorMapSwizzle,
                             CUtensorMapL2promotion, CUtensorMapFloatOOBfill);

void make_map(EncodeFn enc, CUtensorMap* m, const void* ptr, int rank, const cuuint64_t* dims, const cuuint64_t* strides,
              const cuuint32_t* box, CUtensorMapSwizzle sw) {
    const cuuint32_t es[3] = {1, 1, 1};
    enc(m, CU_TENSOR_MAP_DATA_TYPE_BFLOAT16, rank, const_cast<void*>(ptr), dims, strides, box, es, CU_TENSOR_MAP_INTERLEAVE_NONE, sw,
        CU_TENSOR_MAP_L2_PROMOTION_L2_128B, CU_TENSOR_MAP_FLOAT_OOB_FILL_NONE);
}

}

#define SCHED 340, 400, 5, 7900, 150, 3, 9000, 1300
static int g_sched[8] = {SCHED};
#define FORCE_SMALL -1
static int g_small = FORCE_SMALL;

extern "C" void kernel_launch(void* const* d_in, const int* in_sizes, int n_in, void* d_out, int out_size) {
    (void)in_sizes; (void)n_in; (void)out_size;
    static EncodeFn enc = nullptr;
    static void *a_epoch, *a_mail;
    if (!enc) {
        void* fn = nullptr;
        cudaDriverEntryPointQueryResult qr;
        cudaGetDriverEntryPoint("cuTensorMapEncodeTiled", &fn, cudaEnableDefault, &qr);
        enc = (EncodeFn)fn;
        cudaFuncSetAttribute(fused_decode<kBig>, cudaFuncAttributeMaxDynamicSharedMemorySize, smem_bytes(kBig));
        cudaFuncSetAttribute(fused_decode<kSmall>, cudaFuncAttributeMaxDynamicSharedMemorySize, smem_bytes(kSmall));
        cudaGetSymbolAddress(&a_epoch, g_epoch);
        cudaGetSymbolAddress(&a_mail, g_mail);
    }
    CUtensorMap tq, tk, tv, to, tg, tu, td;
    {
        const cuuint64_t d[3] = {4096, 512, 1}, s[2] = {8192, 4194304}; const cuuint32_t bx[3] = {64, 128, 1};
        make_map(enc, &tq, d_in[3], 3, d, s, bx, CU_TENSOR_MAP_SWIZZLE_128B);
    }
    {
        const cuuint64_t d[3] = {64, 131072, 2}, s[2] = {256, 128}; const cuuint32_t bx[3] = {64, 64, 2};
        make_map(enc, &tk, d_in[1], 3, d, s, bx, CU_TENSOR_MAP_SWIZZLE_128B);
        make_map(enc, &tv, d_in[2], 3, d, s, bx, CU_TENSOR_MAP_SWIZZLE_128B);
    }
    {
        const cuuint64_t d[3] = {512, 4096, 1}, s[2] = {1024, 4194304}; const cuuint32_t bx[3] = {64, 128, 1};
        make_map(enc, &to, d_in[4], 3, d, s, bx, CU_TENSOR_MAP_SWIZZLE_128B);
    }
    {
        const cuuint64_t d[2] = {1792, 512}, s[1] = {3584}; const cuuint32_t bx[2] = {32, 128};
        make_map(enc, &tg, d_in[6], 2, d, s, bx, CU_TENSOR_MAP_SWIZZLE_64B);
        make_map(enc, &tu, d_in[7], 2, d, s, bx, CU_TENSOR_MAP_SWIZZLE_64B);
    }
    {
        const cuuint64_t d[3] = {512, 1792, 1}, s[2] = {1024, 1835008}; const cuuint32_t bx[3] = {64, 112, 1};
        make_map(enc, &td, d_in[8], 3, d, s, bx, CU_TENSOR_MAP_SWIZZLE_128B);
    }
    Params p;
    p.x = (const __nv_bfloat16*)d_in[0];
    p.out = (__nv_bfloat16*)d_out;
    p.epoch = (unsigned*)a_epoch;
    p.attn_part = (float*)a_mail;
    p.hh_mail = p.attn_part + 8 * 1024;
    p.pace = g_sched[0]; p.lead = g_sched[1]; p.stag = g_sched[2]; p.mlp_t0 = g_sched[3]; p.mlp_dt = g_sched[4];
    p.mlp_stag = g_sched[5]; p.poll_t0 = g_sched[6]; p.dn_gap = g_sched[7];
    cudaLaunchConfig_t cfg = {};
    cfg.gridDim = dim3(kCtas);
    cfg.blockDim = dim3(kThreads);
    cfg.stream = cudaStreamPerThread;
    cudaLaunchAttribute at[1];
    at[0].id = cudaLaunchAttributeClusterDimension;
    at[0].val.clusterDim.x = 8; at[0].val.clusterDim.y = 1; at[0].val.clusterDim.z = 1;
    cfg.attrs = at;
    cfg.numAttrs = 1;
    if (g_small < 0) {
        int n = 0;
        cfg.dynamicSmemBytes = smem_bytes(kBig);
        cudaError_t e = cudaOccupancyMaxActiveClusters(&n, fused_decode<kBig>, &cfg);
        g_small = (e != cudaSuccess || n < kCtas / 8) ? 1 : 0;
        (void)cudaGetLastError();
    }
    if (g_small) {
        cfg.dynamicSmemBytes = smem_bytes(kSmall);
        cudaLaunchKernelEx(&cfg, fused_decode<kSmall>, tq, tk, tv, to, tg, tu, td, p);
    } else {
        cfg.dynamicSmemBytes = smem_bytes(kBig);
        cudaLaunchKernelEx(&cfg, fused_decode<kBig>, tq, tk, tv, to, tg, tu, td, p);
    }
}
```

```cpp
#include <cuda_runtime.h>
#include <cuda_bf16.h>
#include <cuda.h>
#include <stdint.h>

namespace {

constexpr int kAttn = 64, kMlp = 56, kCtas = kAttn + kMlp;
constexpr int SLOT = 16384;
constexpr int kBig = 13, kSmall = 6;
constexpr int A_XN = 0;
constexpr int A_O = A_XN + 2080;
constexpr int A_Q = A_O + 2080;
constexpr int A_P = A_Q + 1088;
constexpr int A_RS = A_P + 4160;
constexpr int A_OP = A_RS + 2048;
constexpr int A_ST = A_OP + 2176;
constexpr int A_WM = A_ST + 128;
constexpr int A_WS = A_WM + 128;
constexpr int A_GP = A_WS + 128;
constexpr int A_HH = A_XN;
constexpr int A_FIN = A_RS;
constexpr int A_HS = A_OP;
constexpr int A_END = A_GP + 1024;
constexpr int M_H = 0;
constexpr int M_PART = M_H + 2080;
constexpr int M_CSP = M_PART + 6144;
constexpr int M_ONE = M_CSP + 2048;
constexpr int M_ST = M_ONE + 128;
constexpr int M_G3 = M_ST + 16;
constexpr int M_SP = M_G3 + 4096;
constexpr int M_END = M_SP + 128;
constexpr int OFF_BAR = ((A_END > M_END ? A_END : M_END) + 15) / 16 * 16;
constexpr int OFF_PROF = OFF_BAR + 37 * 8 + 8;
constexpr int MISC_BYTES = OFF_PROF + 64;
constexpr int kThreads = 320;
constexpr int smem_bytes(int nslot) { return nslot * SLOT + MISC_BYTES + 1024; }

constexpr int POLL_LIMIT = 200000;
constexpr int MBAR_LIMIT = 1000000;
constexpr int SPIN_LIMIT = 2000000;

struct Params {
    const __nv_bfloat16* x;
    __nv_bfloat16* out;
    unsigned* epoch;
    float* attn_part;
    float* hh_mail;
    int pace, lead, stag, mlp_t0, mlp_dt, mlp_stag, poll_t0, dn_gap;
};

__device__ unsigned g_epoch;
constexpr int kHhStride = 1056;
__device__ __align__(1024) float g_mail[8 * 1024 + 112 * kHhStride];
#define PROF(i) do {} while (0)
#define PROF_DUMP() do {} while (0)
#define PROFL(i) do {} while (0)
__device__ __forceinline__ uint32_t nsclock() { uint32_t c; asm volatile("mov.u32 %0, %%globaltimer_lo;" : "=r"(c) :: "memory"); return c; }
__device__ __forceinline__ uint32_t s2u(const void* p) { return (uint32_t)__cvta_generic_to_shared(p); }
__device__ __forceinline__ void mbar_init(uint32_t a, int c) { asm volatile("mbarrier.init.shared::cta.b64 [%0], %1;" ::"r"(a), "r"(c) : "memory"); }
__device__ __forceinline__ void mbar_expect(uint32_t a, uint32_t b) { asm volatile("mbarrier.arrive.expect_tx.shared::cta.b64 _, [%0], %1;" ::"r"(a), "r"(b) : "memory"); }
__device__ __forceinline__ void mbar_arrive(uint32_t a) { asm volatile("mbarrier.arrive.shared::cta.b64 _, [%0];" ::"r"(a) : "memory"); }
__device__ __forceinline__ void mbar_wait(uint32_t a, uint32_t ph) {
    uint32_t ok; int it = 0;
    do {
        asm volatile("{ .reg .pred p; mbarrier.try_wait.parity.shared::cta.b64 p, [%1], %2, %3; selp.u32 %0, 1, 0, p; }"
                     : "=r"(ok) : "r"(a), "r"(ph), "r"(2000u) : "memory");
    } while (!ok && ++it < MBAR_LIMIT);
}
__device__ __forceinline__ bool mbar_test(uint32_t a, uint32_t ph) {
    uint32_t ok;
    asm volatile("{ .reg .pred p; mbarrier.test_wait.parity.shared::cta.b64 p, [%1], %2; selp.u32 %0, 1, 0, p; }" : "=r"(ok) : "r"(a), "r"(ph) : "memory");
    return ok;
}
__device__ __forceinline__ void tma2d(uint32_t dst, const CUtensorMap* m, int c0, int c1, uint32_t bar) {
    asm volatile("cp.async.bulk.tensor.2d.shared::cluster.global.mbarrier::complete_tx::bytes [%0], [%1, {%3, %4}], [%2];"
                 ::"r"(dst), "l"(m), "r"(bar), "r"(c0), "r"(c1) : "memory");
}
__device__ __forceinline__ void tma3d(uint32_t dst, const CUtensorMap* m, int c0, int c1, int c2, uint32_t bar) {
    asm volatile("cp.async.bulk.tensor.3d.shared::cluster.global.mbarrier::complete_tx::bytes [%0], [%1, {%3, %4, %5}], [%2];"
                 ::"r"(dst), "l"(m), "r"(bar), "r"(c0), "r"(c1), "r"(c2) : "memory");
}
__device__ __forceinline__ uint32_t mapa(uint32_t a, uint32_t rank) { uint32_t r; asm("mapa.shared::cluster.u32 %0, %1, %2;" : "=r"(r) : "r"(a), "r"(rank)); return r; }
__device__ __forceinline__ void st_async4(uint32_t dst, uint32_t a, uint32_t b, uint32_t c, uint32_t d, uint32_t bar) {
    asm volatile("st.async.weak.shared::cluster.mbarrier::complete_tx::bytes.v4.b32 [%0], {%1,%2,%3,%4}, [%5];"
                 ::"r"(dst), "r"(a), "r"(b), "r"(c), "r"(d), "r"(bar) : "memory");
}
__device__ __forceinline__ void ldsm4(uint32_t (&r)[4], uint32_t a) {
    asm volatile("ldmatrix.sync.aligned.m8n8.x4.shared.b16 {%0,%1,%2,%3}, [%4];" : "=r"(r[0]), "=r"(r[1]), "=r"(r[2]), "=r"(r[3]) : "r"(a) : "memory");
}
__device__ __forceinline__ void ldsm4t(uint32_t (&r)[4], uint32_t a) {
    asm volatile("ldmatrix.sync.aligned.m8n8.x4.trans.shared.b16 {%0,%1,%2,%3}, [%4];" : "=r"(r[0]), "=r"(r[1]), "=r"(r[2]), "=r"(r[3]) : "r"(a) : "memory");
}
__device__ __forceinline__ void mma(float (&c)[4], uint32_t a0, uint32_t a1, uint32_t a2, uint32_t a3, uint32_t b0, uint32_t b1) {
    asm volatile("mma.sync.aligned.m16n8k16.row.col.f32.bf16.bf16.f32 {%0,%1,%2,%3}, {%4,%5,%6,%7}, {%8,%9}, {%0,%1,%2,%3};"
                 : "+f"(c[0]), "+f"(c[1]), "+f"(c[2]), "+f"(c[3]) : "r"(a0), "r"(a1), "r"(a2), "r"(a3), "r"(b0), "r"(b1));
}
__device__ __forceinline__ void bar_sync(int id, int n) { asm volatile("bar.sync %0, %1;" ::"r"(id), "r"(n) : "memory"); }
__device__ __forceinline__ void bar_arrive(int id, int n) { asm volatile("bar.arrive %0, %1;" ::"r"(id), "r"(n) : "memory"); }
__device__ __forceinline__ void cluster_arrive() { asm volatile("barrier.cluster.arrive.relaxed.aligned;" ::: "memory"); }
__device__ __forceinline__ void cluster_wait() { asm volatile("barrier.cluster.wait.acquire.aligned;" ::: "memory"); }
__device__ __forceinline__ uint32_t pack2(float lo, float hi) { uint32_t r; asm("cvt.rn.bf16x2.f32 %0, %1, %2;" : "=r"(r) : "f"(hi), "f"(lo)); return r; }
__device__ __forceinline__ float bfr(float v) { return __uint_as_float(pack2(0.f, v)); }
__device__ __forceinline__ float bflo(uint32_t v) { return __uint_as_float(v << 16); }
__device__ __forceinline__ float bfhi(uint32_t v) { return __uint_as_float(v & 0xffff0000u); }
__device__ __forceinline__ float ex2(float v) { float r; asm("ex2.approx.ftz.f32 %0, %1;" : "=f"(r) : "f"(v)); return r; }
__device__ __forceinline__ uint4 ld_poll(const float* p) {
    uint4 v;
    asm volatile("ld.relaxed.gpu.global.v4.u32 {%0,%1,%2,%3}, [%4];" : "=r"(v.x), "=r"(v.y), "=r"(v.z), "=r"(v.w) : "l"(p) : "memory");
    return v;
}
__device__ __forceinline__ void st_mail4(float* p, uint32_t v) {
    asm volatile("st.relaxed.gpu.global.v4.u32 [%0], {%1,%1,%1,%1};" ::"l"(p), "r"(v) : "memory");
}
__device__ __forceinline__ void exch_tag4(float* p, float a, float b, float c, float d, uint32_t tag) {
    const uint32_t x = (__float_as_uint(a) & ~1u) | tag, y = (__float_as_uint(b) & ~1u) | tag;
    const uint32_t z = (__float_as_uint(c) & ~1u) | tag, u = (__float_as_uint(d) & ~1u) | tag;
    asm volatile("{ .reg .b128 t, o; mov.b128 t, {%1, %2}; atom.relaxed.gpu.global.exch.b128 o, [%0], t; }" ::"l"(p),
                 "l"((unsigned long long)x | ((unsigned long long)y << 32)), "l"((unsigned long long)z | ((unsigned long long)u << 32)) : "memory");
}
__device__ __forceinline__ void exch_mail1(float* p, uint32_t x) {
    asm volatile("{ .reg .b32 o; atom.relaxed.gpu.global.exch.b32 o, [%0], %1; }" ::"l"(p), "r"(x) : "memory");
}
__device__ __forceinline__ void st_async2(uint32_t dst, float a, float b, uint32_t bar) {
    asm volatile("st.async.weak.shared::cluster.mbarrier::complete_tx::bytes.v2.b32 [%0], {%1,%2}, [%3];"
                 ::"r"(dst), "r"(__float_as_uint(a)), "r"(__float_as_uint(b)), "r"(bar) : "memory");
}
__device__ __forceinline__ uint2 ld_poll2(const float* p) {
    uint2 v;
    asm volatile("ld.relaxed.gpu.global.v2.u32 {%0,%1}, [%2];" : "=r"(v.x), "=r"(v.y) : "l"(p) : "memory");
    return v;
}
__device__ __forceinline__ void lds4(float (&v)[4], uint32_t a) {
    asm volatile("ld.shared.v4.f32 {%0,%1,%2,%3}, [%4];" : "=f"(v[0]), "=f"(v[1]), "=f"(v[2]), "=f"(v[3]) : "r"(a) : "memory");
}
__device__ __forceinline__ uint4 lds4u(uint32_t a) {
    uint4 v; asm volatile("ld.shared.v4.u32 {%0,%1,%2,%3}, [%4];" : "=r"(v.x), "=r"(v.y), "=r"(v.z), "=r"(v.w) : "r"(a) : "memory"); return v;
}
__device__ __forceinline__ float lds1(uint32_t a) { float v; asm volatile("ld.shared.f32 %0, [%1];" : "=f"(v) : "r"(a) : "memory"); return v; }
__device__ __forceinline__ uint32_t lds1u(uint32_t a) { uint32_t v; asm volatile("ld.shared.u32 %0, [%1];" : "=r"(v) : "r"(a) : "memory"); return v; }
__device__ __forceinline__ void sts1(uint32_t a, float v) { asm volatile("st.shared.f32 [%0], %1;" ::"r"(a), "f"(v) : "memory"); }
__device__ __forceinline__ void sts2(uint32_t a, float v, float w) { asm volatile("st.shared.v2.f32 [%0], {%1,%2};" ::"r"(a), "f"(v), "f"(w) : "memory"); }
__device__ __forceinline__ void sts16(uint32_t a, float v) {
    asm volatile("{ .reg .b16 lo, hi; mov.b32 {lo, hi}, %1; st.shared.u16 [%0], lo; }" ::"r"(a), "r"(pack2(v, 0.f)) : "memory");
}
__device__ __forceinline__ void sts4u(uint32_t a, uint32_t x, uint32_t y, uint32_t z, uint32_t w) {
    asm volatile("st.shared.v4.u32 [%0], {%1,%2,%3,%4};" ::"r"(a), "r"(x), "r"(y), "r"(z), "r"(w) : "memory");
}

__device__ __forceinline__ uint32_t pin(uint32_t v) { return __shfl_sync(0xffffffffu, v, threadIdx.x & 31); }
template <class T>
__device__ __forceinline__ T* pin(T* p) {
    const unsigned long long v = (unsigned long long)p;
    return (T*)((unsigned long long)pin((uint32_t)v) | ((unsigned long long)pin((uint32_t)(v >> 32)) << 32));
}
__device__ __forceinline__ void sts1_if(bool c, uint32_t a, float v) {
    asm volatile("{ .reg .pred p; setp.ne.u32 p, %2, 0; @p st.shared.f32 [%0], %1; }" ::"r"(a), "f"(v), "r"((uint32_t)c) : "memory");
}
__device__ __forceinline__ uint32_t xor_or(uint32_t a, uint32_t b, uint32_t t) {
    uint32_t r; asm("lop3.b32 %0, %1, %2, %3, 0x7e;" : "=r"(r) : "r"(a), "r"(b), "r"(t)); return r;
}
template <int N>
__device__ __forceinline__ float tree_sum(float (&f)[N]) {
#pragma unroll
    for (int d = 1; d < N; d <<= 1)
#pragma unroll
        for (int i = 0; i + d < N; i += 2 * d) f[i] += f[i + d];
    return f[0];
}
__device__ __forceinline__ void spin_until(uint32_t due) {
    int it = 0;
    while ((int)(nsclock() - due) < 0 && ++it < SPIN_LIMIT) {}
}
__device__ __forceinline__ uint4 poll_packet(const float* src, uint32_t tmask) {
    uint4 v;
    int it = 0;
    do {
        v = ld_poll(src);
    } while (__any_sync(0xffffffffu, (xor_or(v.x, v.y, tmask) | xor_or(v.z, v.w, tmask)) & 1u) && ++it < POLL_LIMIT);
    return v;
}

__device__ __forceinline__ float rcp_(float v) { float r; asm("rcp.approx.ftz.f32 %0, %1;" : "=f"(r) : "f"(v)); return r; }
__device__ __forceinline__ float sqrt_(float v) { float r; asm("sqrt.approx.ftz.f32 %0, %1;" : "=f"(r) : "f"(v)); return r; }
__device__ __forceinline__ float ln_rden(float var) { return rcp_(bfr(sqrt_(bfr(bfr(var) + 1e-5f)))); }

template <int NSLOT>
__global__ void __launch_bounds__(kThreads, NSLOT <= 6 ? 2 : 1)
fused_decode(const __grid_constant__ CUtensorMap tm_wq, const __grid_constant__ CUtensorMap tm_k,
             const __grid_constant__ CUtensorMap tm_v, const __grid_constant__ CUtensorMap tm_wo,
             const __grid_constant__ CUtensorMap tm_g, const __grid_constant__ CUtensorMap tm_u,
             const __grid_constant__ CUtensorMap tm_d, const Params p) {
    extern __shared__ uint8_t smem_raw[];
    const uint32_t sb = (s2u(smem_raw) + 1023u) & ~1023u;
    const uint32_t mb_ = sb + NSLOT * SLOT;
    const int t = threadIdx.x, w = t >> 5, lane = t & 31, grp = lane >> 2, hq = lane & 3;
    const int cta = blockIdx.x, r = cta & 7, cl = cta >> 3;
    const uint32_t bar0 = mb_ + OFF_BAR;
    const uint32_t ns0 = nsclock();
#define FULL(s) (bar0 + 8 * (s))
#define EMPTY(s) (bar0 + 128 + 8 * (s))
#define XBAR(i) (bar0 + 256 + 8 * (i))
#define MFULL(i) ((i) < 6 ? FULL(i) : EMPTY((i) - 6))
    if (w == 8) {
        if (lane == 0) {
            mbar_init(FULL(0), 1);
            asm volatile("fence.mbarrier_init.release.cluster;" ::: "memory");
            if (cta < kAttn) { mbar_expect(FULL(0), SLOT); tma3d(sb, &tm_wq, 64 * cta, 0, 0, FULL(0)); }
#pragma unroll
            for (int s = 1; s < NSLOT; s++) mbar_init(FULL(s), 1);
#pragma unroll
            for (int s = 0; s < NSLOT; s++) mbar_init(EMPTY(s), cta < kAttn ? 8 : 1);
            asm volatile("fence.mbarrier_init.release.cluster;" ::: "memory");
        }
        __syncwarp();
        if (cta < kAttn) { if (lane >= 1 && lane < NSLOT) mbar_expect(FULL(lane), SLOT); }
        else if (lane < 8) mbar_expect(MFULL(lane), SLOT / 2);
    }
    if (t == 64) {
#pragma unroll
        for (int i = 0; i < 5; i++) mbar_init(XBAR(i), 1);
        asm volatile("fence.mbarrier_init.release.cluster;" ::: "memory");
        mbar_expect(XBAR(0), 1024);
        mbar_expect(XBAR(1), 128);
        mbar_expect(XBAR(2), cta < kAttn ? 2048 : 128);
        mbar_expect(XBAR(3), 2048);
        mbar_expect(XBAR(4), 1024);
    }
    __syncwarp();
    cluster_arrive();

    if (cta < kAttn) {
        const int g = cl, b = r >> 2, j = r & 3;
        if (w == 9) {
            bar_arrive(0, kThreads);
        } else if (w == 8) {
            bar_arrive(0, kThreads);
            if (lane == 0) {
                const int kvrow = (b * 8 + g) * 8192 + 6144 + 512 * j;
                uint32_t dst = sb + SLOT, fb = FULL(1), fend = FULL(NSLOT), ph = 1;
                asm volatile("" : "+r"(dst), "+r"(fb), "+r"(fend));
                int i = 1;
                const uint32_t pace = p.pace;
                uint32_t due = ns0 - p.lead + ((cta * 37) & 63) * p.stag;
                auto run = [&](const CUtensorMap* m, int c0, int c1, int step, int n, uint32_t bytes) {
#pragma unroll 1
                    for (; n > 0; n--, i++, c1 += step) {
                        if (i >= NSLOT) { mbar_wait(fb + 128, ph); mbar_expect(fb, bytes); }
                        due += pace;
                        spin_until(due);
                        tma3d(dst, m, c0, c1, 0, fb);
                        dst += SLOT; fb += 8;
                        if (fb == fend) { fb -= 8 * NSLOT; dst -= SLOT * NSLOT; ph ^= 1; }
                    }
                };
                run(&tm_wq, 64 * cta, 128, 128, 3, SLOT);
                run(&tm_k, 0, kvrow, 64, 8, SLOT);
                run(&tm_v, 0, kvrow, 64, 8, SLOT);
                run(&tm_wo, 64 * r, 512 * g, 128, 4, SLOT);
                due += p.dn_gap;
                run(&tm_d, 64 * g, 224 * r, 112, 2, 14336);
                PROF(8);
                PROF_DUMP();
            }
            __syncwarp();
            cluster_wait();
        } else {
            if (w < 2) {
                const uint4* xp = reinterpret_cast<const uint4*>(p.x + w * 512 + lane * 16);
                const uint4 xa = __ldg(xp), xb = __ldg(xp + 1);
                const uint32_t u[8] = {xa.x, xa.y, xa.z, xa.w, xb.x, xb.y, xb.z, xb.w};
                float v[16], f[16];
#pragma unroll
                for (int i = 0; i < 8; i++) { v[2 * i] = bflo(u[i]); v[2 * i + 1] = bfhi(u[i]); }
#pragma unroll
                for (int i = 0; i < 16; i++) f[i] = v[i];
                float sm = tree_sum(f);
#pragma unroll
                for (int o = 16; o; o >>= 1) sm += __shfl_xor_sync(0xffffffffu, sm, o);
                const float mean = sm * (1.f / 512.f);
#pragma unroll
                for (int i = 0; i < 16; i++) { const float d = v[i] - mean; f[i] = d * d; }
                float sq = tree_sum(f);
#pragma unroll
                for (int o = 16; o; o >>= 1) sq += __shfl_xor_sync(0xffffffffu, sq, o);
                const float mb = bfr(mean), rden = ln_rden(sq * (1.f / 512.f));
                uint32_t o[8];
#pragma unroll
                for (int i = 0; i < 8; i++) {
                    const uint32_t c = pack2(v[2 * i] - mb, v[2 * i + 1] - mb);
                    o[i] = pack2(bflo(c) * rden, bfhi(c) * rden);
                }
                const uint32_t d = mb_ + A_XN + w * 1040 + lane * 32;
                sts4u(d, o[0], o[1], o[2], o[3]);
                sts4u(d + 16, o[4], o[5], o[6], o[7]);
            }
            unsigned ep;
            asm volatile("ld.relaxed.gpu.global.u32 %0, [%1];" : "=r"(ep) : "l"(p.epoch) : "memory");
            uint2 xr;
            asm volatile("ld.global.nc.v2.u32 {%0,%1}, [%2];" : "=r"(xr.x), "=r"(xr.y) : "l"(p.x + (hq >> 1) * 512 + 8 * cta + (hq & 1) * 4));
            const int mt = w & 3, hp = w >> 2, h0 = 2 * (hq & 1);
            const int mi = lane >> 3, rr = (lane & 7) + (mi >> 1) * 8;
            const uint32_t act_off = (lane & 7) * 1040 + hp * 128 + mi * 16;
            const uint32_t wt_off = sb + (64 * hp + rr) * 128 + (((2 * mt + (mi & 1)) ^ (rr & 7)) << 4);
            uint32_t gp_st = mb_ + A_GP + hp * 512 + (16 * mt + grp) * 4;
            constexpr float L2E = 1.4426950408889634f;
            bar_sync(0, kThreads);
            PROF(0);
            {
                float acc[2][4] = {};
#pragma unroll 1
                for (int i = 0; i < 4; i++) {
                    uint32_t bf[2][4];
                    ldsm4(bf[0], mb_ + A_XN + act_off + i * 256);
                    ldsm4(bf[1], mb_ + A_XN + act_off + i * 256 + 64);
                    mbar_wait(FULL(i), 0);
                    if (i == 0) PROF(2);
#pragma unroll
                    for (int k = 0; k < 4; k++) {
                        uint32_t a[4];
                        ldsm4t(a, wt_off + i * SLOT + k * 2048);
                        mma(acc[k & 1], a[0], a[1], a[2], a[3], bf[k >> 1][(k & 1) * 2], bf[k >> 1][(k & 1) * 2 + 1]);
                    }
                    __syncwarp();
                    if (lane == 0) mbar_arrive(EMPTY(i));
                }
                if (hq == 0) {
                    sts1(gp_st, acc[0][0] + acc[1][0]); sts1(gp_st + 256, acc[0][1] + acc[1][1]);
                    sts1(gp_st + 32, acc[0][2] + acc[1][2]); sts1(gp_st + 256 + 32, acc[0][3] + acc[1][3]);
                }
                cluster_wait();
                bar_sync(1, 256);
                if (w < 2) {
                    const int tg = t >> 3, pc = t & 7;
                    const uint32_t src = mb_ + A_GP + (tg >> 2) * 256 + pc * 32;
                    float u0[4], u1[4], v0[4], v1[4];
                    lds4(u0, src); lds4(u1, src + 16); lds4(v0, src + 512); lds4(v1, src + 512 + 16);
                    st_async4(mapa(mb_ + A_Q + (r >> 1) * 272 + (r & 1) * 128 + pc * 16, tg), pack2(u0[0] + v0[0], u0[1] + v0[1]),
                              pack2(u0[2] + v0[2], u0[3] + v0[3]), pack2(u1[0] + v1[0], u1[1] + v1[1]), pack2(u1[2] + v1[2], u1[3] + v1[3]),
                              mapa(XBAR(0), tg));
                }
            }
            if (w == 2) st_mail4(p.attn_part + g * 1024 + r * 128 + lane * 4, ep & 1);
            PROF(1);
            int s = 4, ph = 0;
            float sc[4][4] = {};
            {
                mbar_wait(XBAR(0), 0);
                uint32_t qf[4][4];
#pragma unroll
                for (int i = 0; i < 4; i++) ldsm4(qf[i], mb_ + A_Q + (lane & 7) * 272 + i * 64 + (lane >> 3) * 16);
                const int row = 16 * mt + (lane & 7) + ((lane >> 3) & 1) * 8;
                const uint32_t x0a = row * 128 + ((((lane >> 4) ^ (row & 7))) << 4);
#pragma unroll 1
                for (int c = 0; c < 8; c++) {
                    if ((c & 1) == hp) {
                        mbar_wait(FULL(s), ph);
                        float s0[4] = {}, s1[4] = {};
                        const uint32_t kb = sb + s * SLOT;
#pragma unroll
                        for (int ks = 0; ks < 8; ks++) {
                            uint32_t a[4];
                            ldsm4(a, kb + (ks >> 2) * 8192 + (x0a ^ ((ks & 3) << 5)));
                            if (ks & 1) mma(s1, a[0], a[1], a[2], a[3], qf[ks >> 1][2], qf[ks >> 1][3]);
                            else mma(s0, a[0], a[1], a[2], a[3], qf[ks >> 1][0], qf[ks >> 1][1]);
                        }
#pragma unroll
                        for (int k = 0; k < 3; k++)
#pragma unroll
                            for (int e = 0; e < 4; e++) sc[k][e] = sc[k + 1][e];
                        const uint32_t r1 = pack2(s0[0] + s1[0], s0[1] + s1[1]), r3 = pack2(s0[2] + s1[2], s0[3] + s1[3]);
                        const uint32_t r2 = pack2(bflo(r1) * 0.08838834764831845f, bfhi(r1) * 0.08838834764831845f);
                        const uint32_t r4 = pack2(bflo(r3) * 0.08838834764831845f, bfhi(r3) * 0.08838834764831845f);
                        sc[3][0] = bflo(r2); sc[3][1] = bfhi(r2); sc[3][2] = bflo(r4); sc[3][3] = bfhi(r4);
                        __syncwarp();
                        if (lane < 2) mbar_arrive(EMPTY(s));
                    }
                    if (++s == NSLOT) { s = 0; ph ^= 1; }
                }
            }
            PROF(3);
            {
                float m0 = fmaxf(fmaxf(fmaxf(sc[0][0], sc[1][0]), fmaxf(sc[2][0], sc[3][0])), fmaxf(fmaxf(sc[0][2], sc[1][2]), fmaxf(sc[2][2], sc[3][2])));
                float m1 = fmaxf(fmaxf(fmaxf(sc[0][1], sc[1][1]), fmaxf(sc[2][1], sc[3][1])), fmaxf(fmaxf(sc[0][3], sc[1][3]), fmaxf(sc[2][3], sc[3][3])));
#pragma unroll
                for (int o = 4; o <= 16; o <<= 1) {
                    m0 = fmaxf(m0, __shfl_xor_sync(0xffffffffu, m0, o));
                    m1 = fmaxf(m1, __shfl_xor_sync(0xffffffffu, m1, o));
                }
                if (lane < 2) { sts1(mb_ + A_WM + h0 * 32 + w * 4, m0); sts1(mb_ + A_WM + h0 * 32 + 32 + w * 4, m1); }
                bar_sync(1, 256);
                float a0[4], a1[4], b0[4], b1[4];
                lds4(a0, mb_ + A_WM + h0 * 32); lds4(a1, mb_ + A_WM + h0 * 32 + 16);
                lds4(b0, mb_ + A_WM + h0 * 32 + 32); lds4(b1, mb_ + A_WM + h0 * 32 + 48);
                m0 = fmaxf(fmaxf(fmaxf(a0[0], a0[1]), fmaxf(a0[2], a0[3])), fmaxf(fmaxf(a1[0], a1[1]), fmaxf(a1[2], a1[3])));
                m1 = fmaxf(fmaxf(fmaxf(b0[0], b0[1]), fmaxf(b0[2], b0[3])), fmaxf(fmaxf(b1[0], b1[1]), fmaxf(b1[2], b1[3])));
                const uint32_t pa = mb_ + A_P + h0 * 1040 + (64 * hp + 16 * mt + grp) * 2;
                float l0 = 0.f, l1 = 0.f;
#pragma unroll
                for (int i = 0; i < 4; i++) {
                    const float e0 = ex2((sc[i][0] - m0) * L2E), e1 = ex2((sc[i][1] - m1) * L2E);
                    const float e2 = ex2((sc[i][2] - m0) * L2E), e3 = ex2((sc[i][3] - m1) * L2E);
                    if (hq < 2) {
                        sts16(pa + i * 256, e0);
                        sts16(pa + i * 256 + 1040, e1);
                        sts16(pa + i * 256 + 16, e2);
                        sts16(pa + i * 256 + 1040 + 16, e3);
                    }
                    l0 += e0 + e2; l1 += e1 + e3;
                }
#pragma unroll
                for (int o = 4; o <= 16; o <<= 1) {
                    l0 += __shfl_xor_sync(0xffffffffu, l0, o);
                    l1 += __shfl_xor_sync(0xffffffffu, l1, o);
                }
                if (lane < 2) { sts1(mb_ + A_WS + h0 * 32 + w * 4, l0); sts1(mb_ + A_WS + h0 * 32 + 32 + w * 4, l1); }
                bar_sync(1, 256);
                if (w == 7) {
                    lds4(a0, mb_ + A_WS + h0 * 32); lds4(a1, mb_ + A_WS + h0 * 32 + 16);
                    lds4(b0, mb_ + A_WS + h0 * 32 + 32); lds4(b1, mb_ + A_WS + h0 * 32 + 48);
                    l0 = ((a0[0] + a0[1]) + (a0[2] + a0[3])) + ((a1[0] + a1[1]) + (a1[2] + a1[3]));
                    l1 = ((b0[0] + b0[1]) + (b0[2] + b0[3])) + ((b1[0] + b1[1]) + (b1[2] + b1[3]));
                    if (lane < 8) {
                        const uint32_t tgt = 4 * b + (lane >> 1);
                        st_async4(mapa(mb_ + A_ST + j * 32 + (lane & 1) * 16, tgt), __float_as_uint(m0), __float_as_uint(l0),
                                  __float_as_uint(m1), __float_as_uint(l1), mapa(XBAR(1), tgt));
                    }
                }
            }
            PROF(4);
            {
                float o0[4] = {}, o1[4] = {};
                const int ch = 2 * w + (mi & 1);
                const uint32_t voff = sb + (ch >> 3) * 8192 + rr * 128 + (((ch & 7) ^ (rr & 7)) << 4);
                const uint32_t poff = mb_ + A_P + (lane & 7) * 1040 + (lane >> 3) * 16;
#pragma unroll 1
                for (int c = 0; c < 8; c++) {
                    uint32_t pf[2][4];
                    ldsm4(pf[0], poff + c * 128);
                    ldsm4(pf[1], poff + c * 128 + 64);
                    mbar_wait(FULL(s), ph);
#pragma unroll
                    for (int ks = 0; ks < 4; ks++) {
                        uint32_t a[4];
                        ldsm4t(a, voff + s * SLOT + ks * 2048);
                        if (ks & 1) mma(o1, a[0], a[1], a[2], a[3], pf[ks >> 1][2], pf[ks >> 1][3]);
                        else mma(o0, a[0], a[1], a[2], a[3], pf[ks >> 1][0], pf[ks >> 1][1]);
                    }
                    __syncwarp();
                    if (lane == 0) mbar_arrive(EMPTY(s));
                    if (++s == NSLOT) { s = 0; ph ^= 1; }
                }
                PROF(5);
                if (hq < 2) {
                    const uint32_t d = mb_ + A_OP + h0 * 544 + (16 * w + grp) * 4;
                    sts1(d, o0[0] + o1[0]);
                    sts1(d + 544, o0[1] + o1[1]);
                    sts1(d + 32, o0[2] + o1[2]);
                    sts1(d + 544 + 32, o0[3] + o1[3]);
                }
            }
            if (w < 4) {
                mbar_wait(XBAR(1), 0);
                float f[4];
                {
                    float mm[4], ll[4];
#pragma unroll
                    for (int i = 0; i < 4; i++) { mm[i] = lds1(mb_ + A_ST + i * 32 + j * 8); ll[i] = lds1(mb_ + A_ST + i * 32 + j * 8 + 4); }
                    const float M = fmaxf(fmaxf(mm[0], mm[1]), fmaxf(mm[2], mm[3]));
#pragma unroll
                    for (int i = 0; i < 4; i++) f[i] = ex2((mm[i] - M) * L2E);
                    const float inv = rcp_((ll[0] * f[0] + ll[1] * f[1]) + (ll[2] * f[2] + ll[3] * f[3]));
#pragma unroll
                    for (int i = 0; i < 4; i++) f[i] *= inv;
                }
                bar_sync(1, 256);
                const uint4 v = lds4u(mb_ + A_OP + w * 544 + lane * 16);
                const uint32_t tgt = 4 * b + w;
                st_async4(mapa(mb_ + A_RS + j * 512 + lane * 16, tgt), v.x, v.y, v.z, v.w, mapa(XBAR(2), tgt));
                const int tg2 = t >> 4, pc = t & 15;
                const uint32_t da = mapa(mb_ + A_O + b * 1040 + j * 256 + pc * 16, tg2), db = mapa(XBAR(3), tg2);
                mbar_wait(XBAR(2), 0);
                float u[4][8];
#pragma unroll
                for (int i = 0; i < 4; i++) {
                    lds4(*reinterpret_cast<float(*)[4]>(&u[i][0]), mb_ + A_RS + i * 512 + pc * 32);
                    lds4(*reinterpret_cast<float(*)[4]>(&u[i][4]), mb_ + A_RS + i * 512 + pc * 32 + 16);
                }
                float o8[8];
#pragma unroll
                for (int k = 0; k < 8; k++) o8[k] = (u[0][k] * f[0] + u[1][k] * f[1]) + (u[2][k] * f[2] + u[3][k] * f[3]);
                st_async4(da, pack2(o8[0], o8[1]), pack2(o8[2], o8[3]), pack2(o8[4], o8[5]), pack2(o8[6], o8[7]), db);
            } else {
                bar_arrive(1, 256);
            }
            const uint32_t tag = pin((ep + 1) & 1);
            {
                float* pub = pin(p.attn_part + g * 1024 + r * 128 + lane * 4);
                const uint32_t oa = pin(mb_ + A_O + act_off), gp_ld = pin(mb_ + A_GP + lane * 16);
                gp_st = pin(gp_st);
                uint32_t wf[3][4][4];
#pragma unroll
                for (int c = 0; c < 3; c++) {
                    mbar_wait(FULL(s), ph);
#pragma unroll
                    for (int k = 0; k < 4; k++) ldsm4t(wf[c][k], wt_off + s * SLOT + k * 2048);
                    if (++s == NSLOT) { s = 0; ph ^= 1; }
                }
                const uint32_t wl = pin(wt_off + s * SLOT), fl = pin(FULL(s));
                mbar_wait(XBAR(3), 0);
                PROF(6);
                uint32_t bf[4][2][4];
#pragma unroll
                for (int c = 0; c < 4; c++) { ldsm4(bf[c][0], oa + c * 256); ldsm4(bf[c][1], oa + c * 256 + 64); }
                float acc[4][4] = {};
#pragma unroll
                for (int c = 0; c < 3; c++)
#pragma unroll
                    for (int k = 0; k < 4; k++)
                        mma(acc[k], wf[c][k][0], wf[c][k][1], wf[c][k][2], wf[c][k][3], bf[c][k >> 1][(k & 1) * 2], bf[c][k >> 1][(k & 1) * 2 + 1]);
                mbar_wait(fl, ph);
                PROF(9);
#pragma unroll
                for (int k = 0; k < 4; k++) {
                    uint32_t a[4];
                    ldsm4t(a, wl + k * 2048);
                    mma(acc[k], a[0], a[1], a[2], a[3], bf[3][k >> 1][(k & 1) * 2], bf[3][k >> 1][(k & 1) * 2 + 1]);
                }
                if (hq == 0) {
                    sts1(gp_st, (acc[0][0] + acc[1][0]) + (acc[2][0] + acc[3][0]));
                    sts1(gp_st + 256, (acc[0][1] + acc[1][1]) + (acc[2][1] + acc[3][1]));
                    sts1(gp_st + 32, (acc[0][2] + acc[1][2]) + (acc[2][2] + acc[3][2]));
                    sts1(gp_st + 256 + 32, (acc[0][3] + acc[1][3]) + (acc[2][3] + acc[3][3]));
                }
                if (w == 2) {
                    bar_sync(1, 256);
                    float u[4], v[4];
                    lds4(u, gp_ld); lds4(v, gp_ld + 512);
                    exch_tag4(pub, u[0] + v[0], u[1] + v[1], u[2] + v[2], u[3] + v[3], tag);
                    PROFL(12);
                } else {
                    bar_arrive(1, 256);
                }
                PROF(7);
            }
            const uint32_t tmask = 0u - tag;
            {
                const float* src = pin(w == 0 ? p.attn_part + grp * 1024 + cl * 128 + (hq >> 1) * 64 + r * 8 + (hq & 1) * 4
                                              : p.hh_mail + ((7 * r + w - 1) * 2 + (lane >> 4)) * kHhStride + (lane & 15) * 2);
                __nv_bfloat16* outp = pin(p.out + (lane & 1) * 512 + 8 * cta + ((lane >> 1) & 7));
                const uint32_t hs = pin(mb_ + A_HH + (lane >> 4) * 464 + (w - 1) * 64 + (lane & 15) * 4);
                const uint32_t hl = pin(mb_ + A_HH + (lane & 7) * 464 + hp * 224 + mi * 16);
                const uint32_t fl = pin(mb_ + A_FIN + (lane >> 4) * 512 + (lane & 15) * 4);
                const uint32_t fd = mb_ + A_FIN + ((2 * r + hp) * 8 + grp) * 8;
                const uint32_t da0 = pin(mapa(fd, 2 * mt)), da1 = pin(mapa(fd, 2 * mt + 1));
                const uint32_t db0 = pin(mapa(XBAR(4), 2 * mt)), db1 = pin(mapa(XBAR(4), 2 * mt + 1));
                if (++s == NSLOT) { s = 0; ph ^= 1; }
                s += hp;
                const uint32_t fdn = pin(FULL(s)), dn = pin(wt_off - hp * 8192 + s * SLOT);
                uint32_t df[7][4];
                auto stage_dn = [&]() {
                    mbar_wait(fdn, ph);
#pragma unroll
                    for (int k = 0; k < 7; k++) ldsm4t(df[k], dn + k * 2048);
                };
                bool early = false;
                if (w == 0) {
                    const uint4 v = poll_packet(src, tmask);
                    float d4[4] = {__uint_as_float(v.x), __uint_as_float(v.y), __uint_as_float(v.z), __uint_as_float(v.w)};
#pragma unroll
                    for (int o = 4; o <= 16; o <<= 1) {
#pragma unroll
                        for (int i = 0; i < 4; i++) d4[i] += __shfl_xor_sync(0xffffffffu, d4[i], o);
                    }
                    if (lane < 4) {
                        const uint32_t d = mb_ + A_HS + (hq & 1) * 32 + (hq >> 1) * 4;
                        sts1(d, bfr(bflo(xr.x) + bfr(d4[0])));
                        sts1(d + 8, bfr(bfhi(xr.x) + bfr(d4[1])));
                        sts1(d + 16, bfr(bflo(xr.y) + bfr(d4[2])));
                        sts1(d + 24, bfr(bfhi(xr.y) + bfr(d4[3])));
                    }
                    PROF(10);
                } else {
                    uint2 v;
                    int it = 0;
                    do {
                        if (!early && __all_sync(0xffffffffu, mbar_test(fdn, ph))) { early = true; stage_dn(); }
                        v = ld_poll2(src);
                    } while (__any_sync(0xffffffffu, xor_or(v.x, v.y, tmask) & 1u) && ++it < POLL_LIMIT);
                    asm volatile("st.shared.u32 [%0], %1;" ::"r"(hs), "r"(__byte_perm(v.x, v.y, 0x7632)) : "memory");
                }
                if (!early) stage_dn();
                bar_sync(3, 256);
                uint32_t bf[4][4];
#pragma unroll
                for (int k = 0; k < 4; k++) ldsm4(bf[k], hl + k * 64);
                float acc[2][4] = {};
#pragma unroll
                for (int k = 0; k < 7; k++) mma(acc[k & 1], df[k][0], df[k][1], df[k][2], df[k][3], bf[k >> 1][(k & 1) * 2], bf[k >> 1][(k & 1) * 2 + 1]);
                if (hq == 0) {
                    st_async2(da0, acc[0][0] + acc[1][0], acc[0][1] + acc[1][1], db0);
                    st_async2(da1, acc[0][2] + acc[1][2], acc[0][3] + acc[1][3], db1);
                }
                if (w == 0) {
                    const float hv = lds1(mb_ + A_HS + (lane & 15) * 4);
                    mbar_wait(XBAR(4), 0);
                    float f[8];
#pragma unroll
                    for (int i = 0; i < 8; i++) f[i] = lds1(fl + i * 64);
                    float d = tree_sum(f);
                    d += __shfl_xor_sync(0xffffffffu, d, 16);
                    if (lane < 16) *reinterpret_cast<unsigned short*>(outp) = (unsigned short)pack2(hv + bfr(d), 0.f);
                    if (cta == 0 && lane == 0) *p.epoch = ep + 1;
                    PROF(11);
                }
            }
            PROF_DUMP();
        }
    } else {
        const int m = cta - kAttn;
        unsigned ep;
        asm volatile("ld.relaxed.gpu.global.u32 %0, [%1];" : "=r"(ep) : "l"(p.epoch) : "memory");
        if (w >= 8) {
            uint2 xv;
            asm volatile("ld.global.nc.v2.u32 {%0,%1}, [%2];" : "=r"(xv.x), "=r"(xv.y) : "l"(p.x + (lane >> 4) * 512 + 64 * r + (lane & 15) * 4));
            bar_sync(0, kThreads);
            cluster_wait();
            const uint32_t dst = mb_ + M_H + (lane >> 4) * 1040 + 128 * r + ((lane & 15) >> 1) * 16;
            const uint32_t sl = pin(mb_ + M_SP + (lane >> 4) * 64), gl = pin(mb_ + M_G3 + lane * 16);
            uint32_t da[4], db[4];
#pragma unroll
            for (int i = 0; i < 4; i++) {
                da[i] = pin(w == 8 ? mapa(dst, 2 * i + (lane & 1)) : mapa(sl + r * 8, lane & 7));
                db[i] = pin(w == 8 ? mapa(XBAR(3), 2 * i + (lane & 1)) : mapa(XBAR(2), lane & 7));
            }
            float xf[4] = {bflo(xv.x), bfhi(xv.x), bflo(xv.y), bfhi(xv.y)};
#pragma unroll
            for (int k = 0; k < 4; k++) xf[k] = __uint_as_float(pin(__float_as_uint(xf[k])));
            if (w == 9 && lane == 0) {
#pragma unroll 1
                for (int i = 0; i < 8; i++) {
                    spin_until(ns0 + p.mlp_t0 + i * p.mlp_dt + ((m * 37) & 63) * p.mlp_stag);
                    tma2d(sb + (i & 1) * 32768 + (i >> 1) * 8192, (i & 1) ? &tm_u : &tm_g, 32 * m, 128 * (i >> 1), MFULL(i));
                }
            }
            __syncwarp();
            bar_sync(3, kThreads);
            float u[8][4], a4[4];
#pragma unroll
            for (int i = 0; i < 8; i++) lds4(u[i], gl + i * 512);
#pragma unroll
            for (int k = 0; k < 4; k++) a4[k] = xf[k] + bfr(((u[0][k] + u[1][k]) + (u[2][k] + u[3][k])) + ((u[4][k] + u[5][k]) + (u[6][k] + u[7][k])));
            const uint32_t hw0 = pack2(a4[0], a4[1]), hw1 = pack2(a4[2], a4[3]);
            if (w == 8) {
                const uint32_t ow0 = __shfl_xor_sync(0xffffffffu, hw0, 1), ow1 = __shfl_xor_sync(0xffffffffu, hw1, 1);
                const bool odd = lane & 1;
                const uint32_t e0 = odd ? ow0 : hw0, e1 = odd ? ow1 : hw1, e2 = odd ? hw0 : ow0, e3 = odd ? hw1 : ow1;
#pragma unroll
                for (int i = 0; i < 4; i++) st_async4(da[i], e0, e1, e2, e3, db[i]);
                PROF(9);
                PROF_DUMP();
            } else {
                const float h0 = bflo(hw0), h1 = bfhi(hw0), h2 = bflo(hw1), h3 = bfhi(hw1);
                float s1 = (h0 + h1) + (h2 + h3), s2 = fmaf(h0, h0, h1 * h1) + fmaf(h2, h2, h3 * h3);
#pragma unroll
                for (int o = 8; o; o >>= 1) { s1 += __shfl_xor_sync(0xffffffffu, s1, o); s2 += __shfl_xor_sync(0xffffffffu, s2, o); }
                if (!(lane & 8))
                    asm volatile("st.async.weak.shared::cluster.mbarrier::complete_tx::bytes.v2.b32 [%0], {%1,%2}, [%3];"
                                 ::"r"(da[0]), "r"(__float_as_uint(s1)), "r"(__float_as_uint(s2)), "r"(db[0]) : "memory");
                mbar_wait(XBAR(2), 0);
                float u0[4], u1[4], u2[4], u3[4];
                lds4(u0, sl); lds4(u1, sl + 16); lds4(u2, sl + 32); lds4(u3, sl + 48);
                const float mean = (((u0[0] + u0[2]) + (u1[0] + u1[2])) + ((u2[0] + u2[2]) + (u3[0] + u3[2]))) * (1.f / 512.f);
                const float msq = (((u0[1] + u0[3]) + (u1[1] + u1[3])) + ((u2[1] + u2[3]) + (u3[1] + u3[3]))) * (1.f / 512.f);
                const float var = fmaxf(fmaf(-mean, mean, msq), 0.f);
                sts2(mb_ + M_ST + (lane >> 4) * 8, bfr(mean), ln_rden(var));
                PROFL(10);
                bar_arrive(2, 288);
            }
        } else {
            if (t < 32) asm volatile("st.shared.u32 [%0], %1;" ::"r"(mb_ + M_ONE + t * 4), "r"(0x3f803f80u) : "memory");
            bar_sync(0, kThreads);
            cluster_wait();
            const int mi = lane >> 3, rr = (lane & 7) + (mi >> 1) * 8;
            const int bb = (w >> 1) & 1, mat = lane >> 4, col = (w & 1) * 16 + (lane & 15);
            float* dout = pin(p.hh_mail + (m * 2 + bb) * kHhStride + col);
            const uint32_t tag = pin((ep + 1) & 1);
            const uint32_t ha = pin(grp < 6 ? mb_ + M_H + (grp & 1) * 1040 + w * 128 + hq * 4 : mb_ + M_ONE + hq * 4);
            const bool h3 = hq == 3;
            const uint32_t ps0 = pin(h3 ? mb_ + M_CSP + w * 256 + grp * 4 : mb_ + M_PART + w * 768 + ((hq >> 1) * 48 + (hq & 1) * 16 + grp) * 4);
            const uint32_t ps1 = pin(ps0 + (h3 ? 32 : 384)), ps2 = pin(ps0 + (h3 ? 64 : 32)), ps3 = pin(ps0 + (h3 ? 96 : 416));
            const uint32_t pd2 = pin(h3 ? 128 : 256), hq1 = pin(hq & 1), hq2 = pin(hq & 2), second = pin(hq == 0 || h3);
            const uint32_t pld = pin(mb_ + M_PART + bb * 384 + (mat * 48 + col) * 4), cld = pin(mb_ + M_CSP + (mat * 32 + col) * 4);
            const uint32_t sld = pin(mb_ + M_ST + bb * 8), xb = pin(XBAR(3));
            const uint32_t g3 = pin(mb_ + M_G3 + w * 512 + lane * 16);
            uint32_t wf[4][4][4];
            const uint32_t fa = MFULL(w & 6), fb = fa + 8;
            bool ready;
            {
                int it = 0;
                do { ready = mbar_test(fa, 0) && mbar_test(fb, 0); } while (!ready && nsclock() - ns0 < (uint32_t)p.poll_t0 && ++it < SPIN_LIMIT);
            }
            ready = __all_sync(0xffffffffu, ready);
            auto stage_gu = [&]() {
                mbar_wait(fa, 0);
                mbar_wait(fb, 0);
#pragma unroll
                for (int tl = 0; tl < 4; tl++)
#pragma unroll
                    for (int ks = 0; ks < 4; ks++) {
                        const int row = 64 * w + 16 * ks + rr;
                        const int ch = 2 * (tl & 1) + (mi & 1);
                        ldsm4t(wf[tl][ks], sb + (tl >> 1) * 32768 + row * 64 + ((ch ^ ((row >> 1) & 3)) << 4));
                    }
                PROF(0);
            };
            if (ready) stage_gu();
            {
                spin_until(ns0 + p.poll_t0);
                const uint4 v = poll_packet(p.attn_part + w * 1024 + r * 128 + lane * 4, 0u - tag);
                sts4u(g3, v.x, v.y, v.z, v.w);
                bar_arrive(3, kThreads);
            }
            if (!ready) stage_gu();
            PROF(4);
            {
                {
                    mbar_wait(xb, 0);
                    PROF(1);
                    uint32_t hf[8];
#pragma unroll
                    for (int k = 0; k < 8; k++) hf[k] = lds1u(ha + k * 16);
                    float c[4][4] = {};
#pragma unroll
                    for (int ks = 0; ks < 4; ks++)
#pragma unroll
                        for (int tl = 0; tl < 4; tl++)
                            mma(c[tl], wf[tl][ks][0], wf[tl][ks][1], wf[tl][ks][2], wf[tl][ks][3], hf[2 * ks], hf[2 * ks + 1]);
                    const float v0 = hq2 ? (hq1 ? c[0][0] : c[2][0]) : (hq1 ? c[1][0] : c[0][0]);
                    const float v1 = hq2 ? (hq1 ? c[0][2] : c[2][1]) : (hq1 ? c[1][1] : c[0][1]);
                    const float v2 = hq2 ? (hq1 ? c[1][0] : c[2][2]) : (hq1 ? c[1][2] : c[0][2]);
                    const float v3 = hq2 ? (hq1 ? c[1][2] : c[2][3]) : (hq1 ? c[1][3] : c[0][3]);
                    sts1(ps0, v0); sts1(ps1, v1); sts1(ps2, v2); sts1(ps3, v3);
                    sts1_if(second, ps0 + pd2, hq2 ? c[2][0] : c[3][0]);
                    sts1_if(second, ps1 + pd2, hq2 ? c[2][2] : c[3][1]);
                    sts1_if(second, ps2 + pd2, hq2 ? c[3][0] : c[3][2]);
                    sts1_if(second, ps3 + pd2, hq2 ? c[3][2] : c[3][3]);
                    if (w < 4) {
                        bar_sync(2, 288);
                        float f[8], cf[8];
#pragma unroll
                        for (int i = 0; i < 8; i++) f[i] = lds1(pld + i * 768);
#pragma unroll
                        for (int i = 0; i < 8; i++) cf[i] = lds1(cld + i * 256);
                        const float mean = lds1(sld), rs = lds1(sld + 4);
                        const float g = bfr(fmaf(-mean, tree_sum(cf), tree_sum(f)) * rs);
                        const float u = __shfl_xor_sync(0xffffffffu, g, 16);
                        const float e = ex2(g * fmaf(g * g, -0.10294324f, -2.3022082f));
                        const float ge = bfr(g * rcp_(1.f + e));
                        if (lane < 16) exch_mail1(dout, pack2(0.f, ge * u) | tag);
                        PROF(2);
                    } else {
                        bar_arrive(2, 288);
                    }
                }
            }
            PROF(3);
            PROF_DUMP();
        }
    }
}

typedef CUresult (*EncodeFn)(CUtensorMap*, CUtensorMapDataType, cuuint32_t, void*, const cuuint64_t*, const cuuint64_t*,
                             const cuuint32_t*, const cuuint32_t*, CUtensorMapInterleave, CUtensorMapSwizzle,
                             CUtensorMapL2promotion, CUtensorMapFloatOOBfill);

void make_map(EncodeFn enc, CUtensorMap* m, const void* ptr, int rank, const cuuint64_t* dims, const cuuint64_t* strides,
              const cuuint32_t* box, CUtensorMapSwizzle sw) {
    const cuuint32_t es[3] = {1, 1, 1};
    enc(m, CU_TENSOR_MAP_DATA_TYPE_BFLOAT16, rank, const_cast<void*>(ptr), dims, strides, box, es, CU_TENSOR_MAP_INTERLEAVE_NONE, sw,
        CU_TENSOR_MAP_L2_PROMOTION_L2_128B, CU_TENSOR_MAP_FLOAT_OOB_FILL_NONE);
}

}

#define SCHED 340, 400, 5, 7900, 150, 3, 9000, 1300
static int g_sched[8] = {SCHED};
#define FORCE_SMALL -1
static int g_small = FORCE_SMALL;

extern "C" void kernel_launch(void* const* d_in, const int* in_sizes, int n_in, void* d_out, int out_size) {
    (void)in_sizes; (void)n_in; (void)out_size;
    static EncodeFn enc = nullptr;
    static void *a_epoch, *a_mail;
    static float tscale = 1.f;
    if (!enc) {
        void* fn = nullptr;
        cudaDriverEntryPointQueryResult qr;
        cudaGetDriverEntryPoint("cuTensorMapEncodeTiled", &fn, cudaEnableDefault, &qr);
        enc = (EncodeFn)fn;
        cudaFuncSetAttribute(fused_decode<kBig>, cudaFuncAttributeMaxDynamicSharedMemorySize, smem_bytes(kBig));
        cudaFuncSetAttribute(fused_decode<kSmall>, cudaFuncAttributeMaxDynamicSharedMemorySize, smem_bytes(kSmall));
        cudaGetSymbolAddress(&a_epoch, g_epoch);
        cudaGetSymbolAddress(&a_mail, g_mail);
        int dev = 0, khz = 0, bits = 0;
        cudaGetDevice(&dev);
        if (cudaDeviceGetAttribute(&khz, cudaDevAttrMemoryClockRate, dev) == cudaSuccess &&
            cudaDeviceGetAttribute(&bits, cudaDevAttrGlobalMemoryBusWidth, dev) == cudaSuccess && khz > 0 && bits > 0)
            tscale = (2619000.f * 5120.f) / ((float)khz * (float)bits);
        if (!(tscale > 0.4f && tscale < 2.5f)) tscale = 1.f;
        (void)cudaGetLastError();
    }
    CUtensorMap tq, tk, tv, to, tg, tu, td;
    {
        const cuuint64_t d[3] = {4096, 512, 1}, s[2] = {8192, 4194304}; const cuuint32_t bx[3] = {64, 128, 1};
        make_map(enc, &tq, d_in[3], 3, d, s, bx, CU_TENSOR_MAP_SWIZZLE_128B);
    }
    {
        const cuuint64_t d[3] = {64, 131072, 2}, s[2] = {256, 128}; const cuuint32_t bx[3] = {64, 64, 2};
        make_map(enc, &tk, d_in[1], 3, d, s, bx, CU_TENSOR_MAP_SWIZZLE_128B);
        make_map(enc, &tv, d_in[2], 3, d, s, bx, CU_TENSOR_MAP_SWIZZLE_128B);
    }
    {
        const cuuint64_t d[3] = {512, 4096, 1}, s[2] = {1024, 4194304}; const cuuint32_t bx[3] = {64, 128, 1};
        make_map(enc, &to, d_in[4], 3, d, s, bx, CU_TENSOR_MAP_SWIZZLE_128B);
    }
    {
        const cuuint64_t d[2] = {1792, 512}, s[1] = {3584}; const cuuint32_t bx[2] = {32, 128};
        make_map(enc, &tg, d_in[6], 2, d, s, bx, CU_TENSOR_MAP_SWIZZLE_64B);
        make_map(enc, &tu, d_in[7], 2, d, s, bx, CU_TENSOR_MAP_SWIZZLE_64B);
    }
    {
        const cuuint64_t d[3] = {512, 1792, 1}, s[2] = {1024, 1835008}; const cuuint32_t bx[3] = {64, 112, 1};
        make_map(enc, &td, d_in[8], 3, d, s, bx, CU_TENSOR_MAP_SWIZZLE_128B);
    }
    Params p;
    p.x = (const __nv_bfloat16*)d_in[0];
    p.out = (__nv_bfloat16*)d_out;
    p.epoch = (unsigned*)a_epoch;
    p.attn_part = (float*)a_mail;
    p.hh_mail = p.attn_part + 8 * 1024;
    auto sc = [&](int i) { return (int)(g_sched[i] * tscale + 0.5f); };
    p.pace = sc(0); p.lead = sc(1); p.stag = sc(2); p.mlp_t0 = sc(3); p.mlp_dt = sc(4);
    p.mlp_stag = sc(5); p.poll_t0 = sc(6); p.dn_gap = sc(7);
    cudaLaunchConfig_t cfg = {};
    cfg.gridDim = dim3(kCtas);
    cfg.blockDim = dim3(kThreads);
    cfg.stream = cudaStreamPerThread;
    cudaLaunchAttribute at[1];
    at[0].id = cudaLaunchAttributeClusterDimension;
    at[0].val.clusterDim.x = 8; at[0].val.clusterDim.y = 1; at[0].val.clusterDim.z = 1;
    cfg.attrs = at;
    cfg.numAttrs = 1;
    if (g_small < 0) {
        int n = 0;
        cfg.dynamicSmemBytes = smem_bytes(kBig);
        cudaError_t e = cudaOccupancyMaxActiveClusters(&n, fused_decode<kBig>, &cfg);
        g_small = (e != cudaSuccess || n < kCtas / 8) ? 1 : 0;
        (void)cudaGetLastError();
    }
    if (g_small) {
        cfg.dynamicSmemBytes = smem_bytes(kSmall);
        cudaLaunchKernelEx(&cfg, fused_decode<kSmall>, tq, tk, tv, to, tg, tu, td, p);
    } else {
        cfg.dynamicSmemBytes = smem_bytes(kBig);
        cudaLaunchKernelEx(&cfg, fused_decode<kBig>, tq, tk, tv, to, tg, tu, td, p);
    }
}
```
